```python
import torch

def _softmax(x, axis=-1):
    return torch.softmax(x, dim=axis)
def _gelu(x):
    return torch.nn.functional.gelu(x, approximate="tanh")
def _silu(x):
    return torch.nn.functional.silu(x)
def _sigmoid(x):
    return torch.sigmoid(x)
def _layernorm(x, axis=-1, eps=1e-5):
    m = x.mean(dim=axis, keepdim=True)
    v = x.var(dim=axis, keepdim=True, unbiased=False)
    return (x - m) / torch.sqrt(v + eps)
def _scatter_add(tgt, idx, src, axis=0):
    return tgt.clone().index_add_(axis, idx, src)
def _segment_sum(src, seg, n):
    out = torch.zeros((n,) + src.shape[1:], dtype=src.dtype)
    return out.index_add_(0, seg, src)
def _pad(x, pw):
    flat = tuple(v for pair in reversed(pw) for v in pair)
    return torch.nn.functional.pad(x, flat)

kernel_name = 'concat_heads__gqa_block_cached__mha_block_cached__near_ridge'

def setup_inputs():

    _w = (lambda a: (lambda t: t.to(torch.bfloat16) if t.is_floating_point() else t)(torch.as_tensor(a)))
    def _A_setup():
        B, Sq, D = 32, 32, 448
        Hq, Hkv, Sk, Dh = 16, 8, 32, 256
        assert Hq % Hkv == 0, (Hq, Hkv)
        return {
            "x": _w((lambda *s: torch.randn(*s, dtype=torch.bfloat16) * 0.8)(B, Sq, D)),
            "k_cache": _w((lambda *s: torch.randn(*s, dtype=torch.bfloat16) * 0.8)(B, Hkv, Sk, Dh)),
            "v_cache": _w((lambda *s: torch.randn(*s, dtype=torch.bfloat16) * 0.05)(B, Hkv, Sk, Dh)),
            "wq": _w((lambda *s: torch.randn(*s, dtype=torch.bfloat16) * 0.8)(D, Hq * Dh) * (D ** -0.5)),
            "wo": _w((lambda *s: torch.randn(*s, dtype=torch.bfloat16) * 0.05)(Hq * Dh, D) * ((Hq * Dh) ** -0.5)),
        }
    _A_in = _A_setup()

    def _B_setup():
        B, Sq, D = 32, 32, 448
        H, Sk, Dh = 16, 32, 256
        return {
            "x": _w((lambda *s: torch.randn(*s, dtype=torch.bfloat16) * 0.8)(B, Sq, D)),
            "k_cache": _w((lambda *s: torch.randn(*s, dtype=torch.bfloat16) * 0.8)(B, H, Sk, Dh)),
            "v_cache": _w((lambda *s: torch.randn(*s, dtype=torch.bfloat16) * 0.05)(B, H, Sk, Dh)),
            "wq": _w((lambda *s: torch.randn(*s, dtype=torch.bfloat16) * 0.8)(D, H * Dh) * (D ** -0.5)),
            "wo": _w((lambda *s: torch.randn(*s, dtype=torch.bfloat16) * 0.05)(H * Dh, D) * ((H * Dh) ** -0.5)),
        }
    _B_in = _B_setup()

    return {
        "A_x": _A_in["x"],
        "A_k_cache": _A_in["k_cache"],
        "A_v_cache": _A_in["v_cache"],
        "A_wq": _A_in["wq"],
        "A_wo": _A_in["wo"],
        "B_x": _B_in["x"],
        "B_k_cache": _B_in["k_cache"],
        "B_v_cache": _B_in["v_cache"],
        "B_wq": _B_in["wq"],
        "B_wo": _B_in["wo"],
    }

def reference(A_x, A_k_cache, A_v_cache, A_wq, A_wo, B_x, B_k_cache, B_v_cache, B_wq, B_wo):
    def _A_ref(x, k_cache, v_cache, wq, wo):
        B, Sq, D = x.shape
        Hq, Dh = 16, 256
        Hkv = k_cache.shape[1]
        rep = Hq // Hkv
        q = (lambda x, *d: x.permute(*d))((x @ wq).reshape(B, Sq, Hq, Dh), 0, 2, 1, 3)
        k = (lambda x, n, axis: torch.repeat_interleave(x, n, dim=axis))(k_cache, rep, axis=1)
        v = (lambda x, n, axis: torch.repeat_interleave(x, n, dim=axis))(v_cache, rep, axis=1)
        scores = torch.einsum("bhqd,bhkd->bhqk", q, k) * (Dh ** -0.5)
        p = _softmax(scores, axis=-1)
        o = torch.einsum("bhqk,bhkd->bhqd", p, v)
        return (lambda x, *d: x.permute(*d))(o, 0, 2, 1, 3).reshape(B, Sq, Hq * Dh) @ wo

    def _B_ref(x, k_cache, v_cache, wq, wo):
        B, Sq, D = x.shape
        H, Dh = 16, 256
        q = (lambda x, *d: x.permute(*d))((x @ wq).reshape(B, Sq, H, Dh), 0, 2, 1, 3)
        scores = torch.einsum("bhqd,bhkd->bhqk", q, k_cache) * (Dh ** -0.5)
        p = _softmax(scores, axis=-1)
        o = torch.einsum("bhqk,bhkd->bhqd", p, v_cache)
        return (lambda x, *d: x.permute(*d))(o, 0, 2, 1, 3).reshape(B, Sq, H * Dh) @ wo

    a = _A_ref(A_x, A_k_cache, A_v_cache, A_wq, A_wo)
    b = _B_ref(B_x, B_k_cache, B_v_cache, B_wq, B_wo)
    return torch.concatenate([a, b], axis=-1)
```

```cpp
#include <cuda_runtime.h>
#include <cuda_bf16.h>
#include <cuda.h>
#include <stdint.h>

namespace {

#define STAG0 4
#define RED_LAG 1
#define RED5_AT 1
#define POLL_NS 50
#define PF_SWITCH 24
#define PREW_N 4

constexpr int SLOT = 16384;
constexpr int NSLOT = 14;
constexpr int NITEMS = 68;
constexpr int B_XFULL = 0;
constexpr int B_FULL = 7;
constexpr int B_KFULL = 79;
constexpr int B_INB = 83;
constexpr int B_EMPTY = 102;
constexpr int B_XEMPTY = 165;
constexpr int B_SINK = 174;
constexpr int NBAR = 175;
constexpr int SMEM_BYTES = 1024 + NSLOT * SLOT + NBAR * 8;
constexpr int TILE = 2048;
constexpr int BOX = 8 * TILE;
constexpr int GRP_BYTES = 50 * BOX;

struct Params {
  CUtensorMap maps[10];
  const unsigned char* ptr[10];
  __nv_bfloat16* out;
};

__device__ __align__(1024) unsigned char g_part[16 * GRP_BYTES];
__device__ unsigned int g_epoch[128 * 8];

#define TS(role, idx)
#define TSC(idx)

__device__ __forceinline__ uint32_t smem_u32(const void* p) { return (uint32_t)__cvta_generic_to_shared(p); }
__device__ __forceinline__ void mbar_init(uint32_t a, uint32_t c) {
  asm volatile("mbarrier.init.shared::cta.b64 [%0], %1;" ::"r"(a), "r"(c) : "memory");
}
__device__ __forceinline__ void mbar_expect(uint32_t a, uint32_t b) {
  asm volatile("mbarrier.arrive.expect_tx.shared::cta.b64 _, [%0], %1;" ::"r"(a), "r"(b) : "memory");
}
__device__ __forceinline__ void mbar_arrive(uint32_t a) {
  asm volatile("mbarrier.arrive.shared::cta.b64 _, [%0];" ::"r"(a) : "memory");
}
__device__ __forceinline__ void mbar_arrive2(uint32_t a) {
  asm volatile("mbarrier.arrive.shared::cta.b64 _, [%0], 2;" ::"r"(a) : "memory");
}
__device__ __forceinline__ void mbar_wait(uint32_t a) {
  asm volatile(
      "{\n.reg .pred P;\n.reg .u32 n;\nmov.u32 n, 0;\n"
      "LW:\nmbarrier.try_wait.parity.shared::cta.b64 P, [%0], 0;\n"
      "@P bra LD;\nadd.u32 n, n, 1;\nsetp.lt.u32 P, n, 0x400000;\n@P bra LW;\n"
      "LD:\n}" ::"r"(a)
      : "memory");
}
__device__ __forceinline__ void mbar_wait_phase(uint32_t a, uint32_t parity) {
  asm volatile(
      "{\n.reg .pred P;\n.reg .u32 n;\nmov.u32 n, 0;\n"
      "LW:\nmbarrier.try_wait.parity.shared::cta.b64 P, [%0], %1;\n"
      "@P bra LD;\nadd.u32 n, n, 1;\nsetp.lt.u32 P, n, 0x400000;\n@P bra LW;\n"
      "LD:\n}" ::"r"(a),
      "r"(parity)
      : "memory");
}
__device__ __forceinline__ void tma_2d(uint32_t dst, const CUtensorMap* m, uint32_t bar, int c0, int c1) {
  asm volatile(
      "cp.async.bulk.tensor.2d.shared::cluster.global.mbarrier::complete_tx::bytes [%0], [%1, {%3, %4}], [%2];" ::"r"(dst),
      "l"((uint64_t)m), "r"(bar), "r"(c0), "r"(c1)
      : "memory");
}
__device__ __forceinline__ void tma_3d(uint32_t dst, const CUtensorMap* m, uint32_t bar, int c0, int c1, int c2) {
  asm volatile(
      "cp.async.bulk.tensor.3d.shared::cluster.global.mbarrier::complete_tx::bytes [%0], [%1, {%3, %4, %5}], [%2];" ::"r"(
          dst),
      "l"((uint64_t)m), "r"(bar), "r"(c0), "r"(c1), "r"(c2)
      : "memory");
}
__device__ __forceinline__ void tma_5d(uint32_t dst, const CUtensorMap* m, uint32_t bar, int c0, int c1, int c2, int c3,
                                       int c4) {
  asm volatile(
      "cp.async.bulk.tensor.5d.shared::cluster.global.mbarrier::complete_tx::bytes [%0], [%1, {%3, %4, %5, %6, %7}], "
      "[%2];" ::"r"(dst),
      "l"((uint64_t)m), "r"(bar), "r"(c0), "r"(c1), "r"(c2), "r"(c3), "r"(c4)
      : "memory");
}
__device__ __forceinline__ uint32_t ld_pf(const void* p) {
  uint32_t v;
  asm volatile("ld.global.cg.L2::256B.u32 %0, [%1];" : "=r"(v) : "l"(p));
  return v;
}
__device__ __forceinline__ void wg_fence() { asm volatile("wgmma.fence.sync.aligned;" ::: "memory"); }
__device__ __forceinline__ void wg_commit() { asm volatile("wgmma.commit_group.sync.aligned;" ::: "memory"); }
template <int N>
__device__ __forceinline__ void wg_wait() {
  asm volatile("wgmma.wait_group.sync.aligned %0;" ::"n"(N) : "memory");
}
template <int OFF, int N>
__device__ __forceinline__ void acc_fence(float (&d)[128]) {
#pragma unroll
  for (int i = 0; i < N; i++) asm volatile("" : "+f"(d[OFF + i])::"memory");
}
__device__ __forceinline__ uint32_t pack_bf16(float lo, float hi) {
  uint32_t r;
  asm("cvt.rn.bf16x2.f32 %0, %1, %2;" : "=r"(r) : "f"(hi), "f"(lo));
  return r;
}
__device__ __forceinline__ float bf_lo(uint32_t v) { return __uint_as_float(v << 16); }
__device__ __forceinline__ float bf_hi(uint32_t v) { return __uint_as_float(v & 0xffff0000u); }
__device__ __forceinline__ float ex2(float x) {
  float r;
  asm("ex2.approx.ftz.f32 %0, %1;" : "=f"(r) : "f"(x));
  return r;
}
__device__ __forceinline__ float rcp(float x) {
  float r;
  asm("rcp.approx.ftz.f32 %0, %1;" : "=f"(r) : "f"(x));
  return r;
}
__device__ __forceinline__ void st_pkt(const void* p, uint32_t off, uint32_t a, uint32_t b, uint32_t c, uint32_t d) {
  asm volatile(
      "{\n.reg .b64 lo, hi, ad;\n.reg .b128 v;\nmov.b64 lo, {%2, %3};\nmov.b64 hi, {%4, %5};\nmov.b128 v, {lo, hi};\n"
      "cvt.u64.u32 ad, %1;\nadd.u64 ad, ad, %0;\nst.relaxed.gpu.global.b128 [ad], v;\n}" ::"l"(p),
      "r"(off), "r"(a), "r"(b), "r"(c), "r"(d)
      : "memory");
}
__device__ __forceinline__ void ld_pkt2(const void* p, uint32_t off, uint32_t* v) {
  asm volatile(
      "{\n.reg .b64 lo, hi, ad;\n.reg .b128 v, w;\ncvt.u64.u32 ad, %9;\nadd.u64 ad, ad, %8;\n"
      "ld.relaxed.gpu.global.b128 v, [ad];\nld.relaxed.gpu.global.b128 w, [ad+512];\n"
      "mov.b128 {lo, hi}, v;\nmov.b64 {%0, %1}, lo;\nmov.b64 {%2, %3}, hi;\n"
      "mov.b128 {lo, hi}, w;\nmov.b64 {%4, %5}, lo;\nmov.b64 {%6, %7}, hi;\n}"
      : "=r"(v[0]), "=r"(v[1]), "=r"(v[2]), "=r"(v[3]), "=r"(v[4]), "=r"(v[5]), "=r"(v[6]), "=r"(v[7])
      : "l"(p), "r"(off)
      : "memory");
}
__device__ __forceinline__ uint64_t make_desc(uint32_t addr, uint32_t lbo, uint32_t sbo) {
  return (uint64_t)((addr & 0x3FFFF) >> 4) | ((uint64_t)(lbo >> 4) << 16) | ((uint64_t)(sbo >> 4) << 32) |
         ((uint64_t)1 << 62);
}

__device__ __forceinline__ void wgmma_ss_n256(float (&d)[128], uint64_t da, uint64_t db) {
  asm volatile(
    "wgmma.mma_async.sync.aligned.m64n256k16.f32.bf16.bf16 {%0, %1, %2, %3, %4, %5, %6, %7, %8, %9, %10, %11, %12, %13, %14, %15, %16, %17, %18, %19, %20, %21, %22, %23, %24, %25, %26, %27, %28, %29, %30, %31, %32, %33, %34, %35, %36, %37, %38, %39, %40, %41, %42, %43, %44, %45, %46, %47, %48, %49, %50, %51, %52, %53, %54, %55, %56, %57, %58, %59, %60, %61, %62, %63, %64, %65, %66, %67, %68, %69, %70, %71, %72, %73, %74, %75, %76, %77, %78, %79, %80, %81, %82, %83, %84, %85, %86, %87, %88, %89, %90, %91, %92, %93, %94, %95, %96, %97, %98, %99, %100, %101, %102, %103, %104, %105, %106, %107, %108, %109, %110, %111, %112, %113, %114, %115, %116, %117, %118, %119, %120, %121, %122, %123, %124, %125, %126, %127}, %128, %129, 1, 1, 1, 0, 1;\n"
    : "+f"(d[0]), "+f"(d[1]), "+f"(d[2]), "+f"(d[3]), "+f"(d[4]), "+f"(d[5]), "+f"(d[6]), "+f"(d[7]), "+f"(d[8]), "+f"(d[9]), "+f"(d[10]), "+f"(d[11]), "+f"(d[12]), "+f"(d[13]), "+f"(d[14]), "+f"(d[15]), "+f"(d[16]), "+f"(d[17]), "+f"(d[18]), "+f"(d[19]), "+f"(d[20]), "+f"(d[21]), "+f"(d[22]), "+f"(d[23]), "+f"(d[24]), "+f"(d[25]), "+f"(d[26]), "+f"(d[27]), "+f"(d[28]), "+f"(d[29]), "+f"(d[30]), "+f"(d[31]), "+f"(d[32]), "+f"(d[33]), "+f"(d[34]), "+f"(d[35]), "+f"(d[36]), "+f"(d[37]), "+f"(d[38]), "+f"(d[39]), "+f"(d[40]), "+f"(d[41]), "+f"(d[42]), "+f"(d[43]), "+f"(d[44]), "+f"(d[45]), "+f"(d[46]), "+f"(d[47]), "+f"(d[48]), "+f"(d[49]), "+f"(d[50]), "+f"(d[51]), "+f"(d[52]), "+f"(d[53]), "+f"(d[54]), "+f"(d[55]), "+f"(d[56]), "+f"(d[57]), "+f"(d[58]), "+f"(d[59]), "+f"(d[60]), "+f"(d[61]), "+f"(d[62]), "+f"(d[63]), "+f"(d[64]), "+f"(d[65]), "+f"(d[66]), "+f"(d[67]), "+f"(d[68]), "+f"(d[69]), "+f"(d[70]), "+f"(d[71]), "+f"(d[72]), "+f"(d[73]), "+f"(d[74]), "+f"(d[75]), "+f"(d[76]), "+f"(d[77]), "+f"(d[78]), "+f"(d[79]), "+f"(d[80]), "+f"(d[81]), "+f"(d[82]), "+f"(d[83]), "+f"(d[84]), "+f"(d[85]), "+f"(d[86]), "+f"(d[87]), "+f"(d[88]), "+f"(d[89]), "+f"(d[90]), "+f"(d[91]), "+f"(d[92]), "+f"(d[93]), "+f"(d[94]), "+f"(d[95]), "+f"(d[96]), "+f"(d[97]), "+f"(d[98]), "+f"(d[99]), "+f"(d[100]), "+f"(d[101]), "+f"(d[102]), "+f"(d[103]), "+f"(d[104]), "+f"(d[105]), "+f"(d[106]), "+f"(d[107]), "+f"(d[108]), "+f"(d[109]), "+f"(d[110]), "+f"(d[111]), "+f"(d[112]), "+f"(d[113]), "+f"(d[114]), "+f"(d[115]), "+f"(d[116]), "+f"(d[117]), "+f"(d[118]), "+f"(d[119]), "+f"(d[120]), "+f"(d[121]), "+f"(d[122]), "+f"(d[123]), "+f"(d[124]), "+f"(d[125]), "+f"(d[126]), "+f"(d[127])
    : "l"(da), "l"(db));
}

template <int OFF, int IMM>
__device__ __forceinline__ void wgmma_sp_n128(float (&d)[128], const uint32_t* a, uint32_t base, uint32_t meta) {
  asm volatile(
    "{\n.reg .b32 lo;\n.reg .b64 db;\nadd.u32 lo, %68, %70;\nmov.b64 db, {lo, 0x40000040};\n"
    "wgmma.mma_async.sp.sync.aligned.m64n128k32.f32.bf16.bf16 {%0, %1, %2, %3, %4, %5, %6, %7, %8, %9, %10, %11, %12, %13, %14, %15, %16, %17, %18, %19, %20, %21, %22, %23, %24, %25, %26, %27, %28, %29, %30, %31, %32, %33, %34, %35, %36, %37, %38, %39, %40, %41, %42, %43, %44, %45, %46, %47, %48, %49, %50, %51, %52, %53, %54, %55, %56, %57, %58, %59, %60, %61, %62, %63}, {%64, %65, %66, %67}, db, %69, 0, 1, 1, 1, 1;\n}\n"
    : "+f"(d[OFF + 0]), "+f"(d[OFF + 1]), "+f"(d[OFF + 2]), "+f"(d[OFF + 3]), "+f"(d[OFF + 4]), "+f"(d[OFF + 5]), "+f"(d[OFF + 6]), "+f"(d[OFF + 7]), "+f"(d[OFF + 8]), "+f"(d[OFF + 9]), "+f"(d[OFF + 10]), "+f"(d[OFF + 11]), "+f"(d[OFF + 12]), "+f"(d[OFF + 13]), "+f"(d[OFF + 14]), "+f"(d[OFF + 15]), "+f"(d[OFF + 16]), "+f"(d[OFF + 17]), "+f"(d[OFF + 18]), "+f"(d[OFF + 19]), "+f"(d[OFF + 20]), "+f"(d[OFF + 21]), "+f"(d[OFF + 22]), "+f"(d[OFF + 23]), "+f"(d[OFF + 24]), "+f"(d[OFF + 25]), "+f"(d[OFF + 26]), "+f"(d[OFF + 27]), "+f"(d[OFF + 28]), "+f"(d[OFF + 29]), "+f"(d[OFF + 30]), "+f"(d[OFF + 31]), "+f"(d[OFF + 32]), "+f"(d[OFF + 33]), "+f"(d[OFF + 34]), "+f"(d[OFF + 35]), "+f"(d[OFF + 36]), "+f"(d[OFF + 37]), "+f"(d[OFF + 38]), "+f"(d[OFF + 39]), "+f"(d[OFF + 40]), "+f"(d[OFF + 41]), "+f"(d[OFF + 42]), "+f"(d[OFF + 43]), "+f"(d[OFF + 44]), "+f"(d[OFF + 45]), "+f"(d[OFF + 46]), "+f"(d[OFF + 47]), "+f"(d[OFF + 48]), "+f"(d[OFF + 49]), "+f"(d[OFF + 50]), "+f"(d[OFF + 51]), "+f"(d[OFF + 52]), "+f"(d[OFF + 53]), "+f"(d[OFF + 54]), "+f"(d[OFF + 55]), "+f"(d[OFF + 56]), "+f"(d[OFF + 57]), "+f"(d[OFF + 58]), "+f"(d[OFF + 59]), "+f"(d[OFF + 60]), "+f"(d[OFF + 61]), "+f"(d[OFF + 62]), "+f"(d[OFF + 63])
    : "r"(a[0]), "r"(a[1]), "r"(a[2]), "r"(a[3]), "r"(base), "r"(meta), "n"(IMM));
}

template <int TB, int OFF, int IMM>
__device__ __forceinline__ void wgmma_rs_n64(float (&d)[128], const uint32_t* a, uint32_t base) {
  asm volatile(
    "{\n.reg .b32 lo;\n.reg .b64 db;\nadd.u32 lo, %36, %38;\nmov.b64 db, {lo, 0x40000040};\n"
    "wgmma.mma_async.sync.aligned.m64n64k16.f32.bf16.bf16 {%0, %1, %2, %3, %4, %5, %6, %7, %8, %9, %10, %11, %12, %13, %14, %15, %16, %17, %18, %19, %20, %21, %22, %23, %24, %25, %26, %27, %28, %29, %30, %31}, {%32, %33, %34, %35}, db, 1, 1, 1, %37;\n}\n"
    : "+f"(d[OFF + 0]), "+f"(d[OFF + 1]), "+f"(d[OFF + 2]), "+f"(d[OFF + 3]), "+f"(d[OFF + 4]), "+f"(d[OFF + 5]), "+f"(d[OFF + 6]), "+f"(d[OFF + 7]), "+f"(d[OFF + 8]), "+f"(d[OFF + 9]), "+f"(d[OFF + 10]), "+f"(d[OFF + 11]), "+f"(d[OFF + 12]), "+f"(d[OFF + 13]), "+f"(d[OFF + 14]), "+f"(d[OFF + 15]), "+f"(d[OFF + 16]), "+f"(d[OFF + 17]), "+f"(d[OFF + 18]), "+f"(d[OFF + 19]), "+f"(d[OFF + 20]), "+f"(d[OFF + 21]), "+f"(d[OFF + 22]), "+f"(d[OFF + 23]), "+f"(d[OFF + 24]), "+f"(d[OFF + 25]), "+f"(d[OFF + 26]), "+f"(d[OFF + 27]), "+f"(d[OFF + 28]), "+f"(d[OFF + 29]), "+f"(d[OFF + 30]), "+f"(d[OFF + 31])
    : "r"(a[0]), "r"(a[1]), "r"(a[2]), "r"(a[3]), "r"(base), "n"(TB), "n"(IMM));
}

__device__ __forceinline__ void wgmma_ss_n256_init(float (&d)[128], uint64_t da, uint64_t db) {
  asm volatile(
    "wgmma.mma_async.sync.aligned.m64n256k16.f32.bf16.bf16 {%0, %1, %2, %3, %4, %5, %6, %7, %8, %9, %10, %11, %12, %13, %14, %15, %16, %17, %18, %19, %20, %21, %22, %23, %24, %25, %26, %27, %28, %29, %30, %31, %32, %33, %34, %35, %36, %37, %38, %39, %40, %41, %42, %43, %44, %45, %46, %47, %48, %49, %50, %51, %52, %53, %54, %55, %56, %57, %58, %59, %60, %61, %62, %63, %64, %65, %66, %67, %68, %69, %70, %71, %72, %73, %74, %75, %76, %77, %78, %79, %80, %81, %82, %83, %84, %85, %86, %87, %88, %89, %90, %91, %92, %93, %94, %95, %96, %97, %98, %99, %100, %101, %102, %103, %104, %105, %106, %107, %108, %109, %110, %111, %112, %113, %114, %115, %116, %117, %118, %119, %120, %121, %122, %123, %124, %125, %126, %127}, %128, %129, 0, 1, 1, 0, 1;\n"
    : "=f"(d[0]), "=f"(d[1]), "=f"(d[2]), "=f"(d[3]), "=f"(d[4]), "=f"(d[5]), "=f"(d[6]), "=f"(d[7]), "=f"(d[8]), "=f"(d[9]), "=f"(d[10]), "=f"(d[11]), "=f"(d[12]), "=f"(d[13]), "=f"(d[14]), "=f"(d[15]), "=f"(d[16]), "=f"(d[17]), "=f"(d[18]), "=f"(d[19]), "=f"(d[20]), "=f"(d[21]), "=f"(d[22]), "=f"(d[23]), "=f"(d[24]), "=f"(d[25]), "=f"(d[26]), "=f"(d[27]), "=f"(d[28]), "=f"(d[29]), "=f"(d[30]), "=f"(d[31]), "=f"(d[32]), "=f"(d[33]), "=f"(d[34]), "=f"(d[35]), "=f"(d[36]), "=f"(d[37]), "=f"(d[38]), "=f"(d[39]), "=f"(d[40]), "=f"(d[41]), "=f"(d[42]), "=f"(d[43]), "=f"(d[44]), "=f"(d[45]), "=f"(d[46]), "=f"(d[47]), "=f"(d[48]), "=f"(d[49]), "=f"(d[50]), "=f"(d[51]), "=f"(d[52]), "=f"(d[53]), "=f"(d[54]), "=f"(d[55]), "=f"(d[56]), "=f"(d[57]), "=f"(d[58]), "=f"(d[59]), "=f"(d[60]), "=f"(d[61]), "=f"(d[62]), "=f"(d[63]), "=f"(d[64]), "=f"(d[65]), "=f"(d[66]), "=f"(d[67]), "=f"(d[68]), "=f"(d[69]), "=f"(d[70]), "=f"(d[71]), "=f"(d[72]), "=f"(d[73]), "=f"(d[74]), "=f"(d[75]), "=f"(d[76]), "=f"(d[77]), "=f"(d[78]), "=f"(d[79]), "=f"(d[80]), "=f"(d[81]), "=f"(d[82]), "=f"(d[83]), "=f"(d[84]), "=f"(d[85]), "=f"(d[86]), "=f"(d[87]), "=f"(d[88]), "=f"(d[89]), "=f"(d[90]), "=f"(d[91]), "=f"(d[92]), "=f"(d[93]), "=f"(d[94]), "=f"(d[95]), "=f"(d[96]), "=f"(d[97]), "=f"(d[98]), "=f"(d[99]), "=f"(d[100]), "=f"(d[101]), "=f"(d[102]), "=f"(d[103]), "=f"(d[104]), "=f"(d[105]), "=f"(d[106]), "=f"(d[107]), "=f"(d[108]), "=f"(d[109]), "=f"(d[110]), "=f"(d[111]), "=f"(d[112]), "=f"(d[113]), "=f"(d[114]), "=f"(d[115]), "=f"(d[116]), "=f"(d[117]), "=f"(d[118]), "=f"(d[119]), "=f"(d[120]), "=f"(d[121]), "=f"(d[122]), "=f"(d[123]), "=f"(d[124]), "=f"(d[125]), "=f"(d[126]), "=f"(d[127])
    : "l"(da), "l"(db));
}

template <int OFF, int IMM>
__device__ __forceinline__ void wgmma_sp_n128_init(float (&d)[128], const uint32_t* a, uint32_t base, uint32_t meta) {
  asm volatile(
    "{\n.reg .b32 lo;\n.reg .b64 db;\nadd.u32 lo, %68, %70;\nmov.b64 db, {lo, 0x40000040};\n"
    "wgmma.mma_async.sp.sync.aligned.m64n128k32.f32.bf16.bf16 {%0, %1, %2, %3, %4, %5, %6, %7, %8, %9, %10, %11, %12, %13, %14, %15, %16, %17, %18, %19, %20, %21, %22, %23, %24, %25, %26, %27, %28, %29, %30, %31, %32, %33, %34, %35, %36, %37, %38, %39, %40, %41, %42, %43, %44, %45, %46, %47, %48, %49, %50, %51, %52, %53, %54, %55, %56, %57, %58, %59, %60, %61, %62, %63}, {%64, %65, %66, %67}, db, %69, 0, 0, 1, 1, 1;\n}\n"
    : "=f"(d[OFF + 0]), "=f"(d[OFF + 1]), "=f"(d[OFF + 2]), "=f"(d[OFF + 3]), "=f"(d[OFF + 4]), "=f"(d[OFF + 5]), "=f"(d[OFF + 6]), "=f"(d[OFF + 7]), "=f"(d[OFF + 8]), "=f"(d[OFF + 9]), "=f"(d[OFF + 10]), "=f"(d[OFF + 11]), "=f"(d[OFF + 12]), "=f"(d[OFF + 13]), "=f"(d[OFF + 14]), "=f"(d[OFF + 15]), "=f"(d[OFF + 16]), "=f"(d[OFF + 17]), "=f"(d[OFF + 18]), "=f"(d[OFF + 19]), "=f"(d[OFF + 20]), "=f"(d[OFF + 21]), "=f"(d[OFF + 22]), "=f"(d[OFF + 23]), "=f"(d[OFF + 24]), "=f"(d[OFF + 25]), "=f"(d[OFF + 26]), "=f"(d[OFF + 27]), "=f"(d[OFF + 28]), "=f"(d[OFF + 29]), "=f"(d[OFF + 30]), "=f"(d[OFF + 31]), "=f"(d[OFF + 32]), "=f"(d[OFF + 33]), "=f"(d[OFF + 34]), "=f"(d[OFF + 35]), "=f"(d[OFF + 36]), "=f"(d[OFF + 37]), "=f"(d[OFF + 38]), "=f"(d[OFF + 39]), "=f"(d[OFF + 40]), "=f"(d[OFF + 41]), "=f"(d[OFF + 42]), "=f"(d[OFF + 43]), "=f"(d[OFF + 44]), "=f"(d[OFF + 45]), "=f"(d[OFF + 46]), "=f"(d[OFF + 47]), "=f"(d[OFF + 48]), "=f"(d[OFF + 49]), "=f"(d[OFF + 50]), "=f"(d[OFF + 51]), "=f"(d[OFF + 52]), "=f"(d[OFF + 53]), "=f"(d[OFF + 54]), "=f"(d[OFF + 55]), "=f"(d[OFF + 56]), "=f"(d[OFF + 57]), "=f"(d[OFF + 58]), "=f"(d[OFF + 59]), "=f"(d[OFF + 60]), "=f"(d[OFF + 61]), "=f"(d[OFF + 62]), "=f"(d[OFF + 63])
    : "r"(a[0]), "r"(a[1]), "r"(a[2]), "r"(a[3]), "r"(base), "r"(meta), "n"(IMM));
}

template <int TB, int OFF, int IMM>
__device__ __forceinline__ void wgmma_rs_n64_init(float (&d)[128], const uint32_t* a, uint32_t base) {
  asm volatile(
    "{\n.reg .b32 lo;\n.reg .b64 db;\nadd.u32 lo, %36, %38;\nmov.b64 db, {lo, 0x40000040};\n"
    "wgmma.mma_async.sync.aligned.m64n64k16.f32.bf16.bf16 {%0, %1, %2, %3, %4, %5, %6, %7, %8, %9, %10, %11, %12, %13, %14, %15, %16, %17, %18, %19, %20, %21, %22, %23, %24, %25, %26, %27, %28, %29, %30, %31}, {%32, %33, %34, %35}, db, 0, 1, 1, %37;\n}\n"
    : "=f"(d[OFF + 0]), "=f"(d[OFF + 1]), "=f"(d[OFF + 2]), "=f"(d[OFF + 3]), "=f"(d[OFF + 4]), "=f"(d[OFF + 5]), "=f"(d[OFF + 6]), "=f"(d[OFF + 7]), "=f"(d[OFF + 8]), "=f"(d[OFF + 9]), "=f"(d[OFF + 10]), "=f"(d[OFF + 11]), "=f"(d[OFF + 12]), "=f"(d[OFF + 13]), "=f"(d[OFF + 14]), "=f"(d[OFF + 15]), "=f"(d[OFF + 16]), "=f"(d[OFF + 17]), "=f"(d[OFF + 18]), "=f"(d[OFF + 19]), "=f"(d[OFF + 20]), "=f"(d[OFF + 21]), "=f"(d[OFF + 22]), "=f"(d[OFF + 23]), "=f"(d[OFF + 24]), "=f"(d[OFF + 25]), "=f"(d[OFF + 26]), "=f"(d[OFF + 27]), "=f"(d[OFF + 28]), "=f"(d[OFF + 29]), "=f"(d[OFF + 30]), "=f"(d[OFF + 31])
    : "r"(a[0]), "r"(a[1]), "r"(a[2]), "r"(a[3]), "r"(base), "n"(TB), "n"(IMM));
}

template <int OFF, int IMM>
__device__ __forceinline__ void wgmma_rs_n32(float (&d)[128], const uint32_t* a, uint32_t base) {
  asm volatile(
    "{\n.reg .b32 lo;\n.reg .b64 db;\nadd.u32 lo, %20, %21;\nmov.b64 db, {lo, 0x40000040};\n"
    "wgmma.mma_async.sync.aligned.m64n32k16.f32.bf16.bf16 {%0, %1, %2, %3, %4, %5, %6, %7, %8, %9, %10, %11, %12, %13, %14, %15}, {%16, %17, %18, %19}, db, 1, 1, 1, 1;\n}\n"
    : "+f"(d[OFF + 0]), "+f"(d[OFF + 1]), "+f"(d[OFF + 2]), "+f"(d[OFF + 3]), "+f"(d[OFF + 4]), "+f"(d[OFF + 5]), "+f"(d[OFF + 6]), "+f"(d[OFF + 7]), "+f"(d[OFF + 8]), "+f"(d[OFF + 9]), "+f"(d[OFF + 10]), "+f"(d[OFF + 11]), "+f"(d[OFF + 12]), "+f"(d[OFF + 13]), "+f"(d[OFF + 14]), "+f"(d[OFF + 15])
    : "r"(a[0]), "r"(a[1]), "r"(a[2]), "r"(a[3]), "r"(base), "n"(IMM));
}

template <int OFF, int IMM>
__device__ __forceinline__ void wgmma_rs_n32_init(float (&d)[128], const uint32_t* a, uint32_t base) {
  asm volatile(
    "{\n.reg .b32 lo;\n.reg .b64 db;\nadd.u32 lo, %20, %21;\nmov.b64 db, {lo, 0x40000040};\n"
    "wgmma.mma_async.sync.aligned.m64n32k16.f32.bf16.bf16 {%0, %1, %2, %3, %4, %5, %6, %7, %8, %9, %10, %11, %12, %13, %14, %15}, {%16, %17, %18, %19}, db, 0, 1, 1, 1;\n}\n"
    : "=f"(d[OFF + 0]), "=f"(d[OFF + 1]), "=f"(d[OFF + 2]), "=f"(d[OFF + 3]), "=f"(d[OFF + 4]), "=f"(d[OFF + 5]), "=f"(d[OFF + 6]), "=f"(d[OFF + 7]), "=f"(d[OFF + 8]), "=f"(d[OFF + 9]), "=f"(d[OFF + 10]), "=f"(d[OFF + 11]), "=f"(d[OFF + 12]), "=f"(d[OFF + 13]), "=f"(d[OFF + 14]), "=f"(d[OFF + 15])
    : "r"(a[0]), "r"(a[1]), "r"(a[2]), "r"(a[3]), "r"(base), "n"(IMM));
}

template <int OFF, bool INIT, int IMM>
__device__ __forceinline__ void g2_group(float (&d)[128], const uint32_t* a, uint32_t base) {
  if (INIT) wgmma_rs_n64_init<1, OFF, IMM>(d, a, base);
  else wgmma_rs_n64<1, OFF, IMM>(d, a, base);
  wgmma_rs_n64<1, OFF, IMM + 128>(d, a + 4, base);
  wgmma_rs_n64<1, OFF, IMM + 256>(d, a + 8, base);
  wgmma_rs_n64<1, OFF, IMM + 384>(d, a + 12, base);
  wgmma_rs_n64<1, OFF, IMM + 512>(d, a + 16, base);
  wgmma_rs_n64<1, OFF, IMM + 640>(d, a + 20, base);
  wgmma_rs_n64<1, OFF, IMM + 768>(d, a + 24, base);
  wgmma_rs_n64<1, OFF, IMM + 896>(d, a + 28, base);
}

template <int OFF, bool INIT, int IMM>
__device__ __forceinline__ void g2_group32(float (&d)[128], const uint32_t* a, uint32_t base) {
  if (INIT) wgmma_rs_n32_init<OFF, IMM>(d, a, base);
  else wgmma_rs_n32<OFF, IMM>(d, a, base);
  wgmma_rs_n32<OFF, IMM + 128>(d, a + 4, base);
  wgmma_rs_n32<OFF, IMM + 256>(d, a + 8, base);
  wgmma_rs_n32<OFF, IMM + 384>(d, a + 12, base);
  wgmma_rs_n32<OFF, IMM + 512>(d, a + 16, base);
  wgmma_rs_n32<OFF, IMM + 640>(d, a + 20, base);
  wgmma_rs_n32<OFF, IMM + 768>(d, a + 24, base);
  wgmma_rs_n32<OFF, IMM + 896>(d, a + 28, base);
}

template <int I>
struct IC { static constexpr int value = I; };
template <int B, int E, class F>
__device__ __forceinline__ void static_for(F&& f) {
  if constexpr (B < E) {
    f(IC<B>{});
    static_for<B + 1, E>(f);
  }
}

__host__ __device__ constexpr int xslot(int k) { return (k & 1) ? 4 + (k >> 1) : (k >> 1); }
enum { K_V0, K_K1, K_V1, K_WI, K_W };
__host__ __device__ constexpr int n_kind(int n) {
  constexpr int t[16] = {K_V0, K_V0, K_WI, K_WI, K_V0, K_V0, K_WI, K_WI, K_K1, K_K1, K_V1, K_V1, K_K1, K_K1, K_V1, K_V1};
  return n < 16 ? t[n] : K_W;
}
__host__ __device__ constexpr int n_a(int n) {
  constexpr int t[16] = {0, 0, 0, 1, 1, 1, 2, 3, 0, 0, 0, 0, 1, 1, 1, 1};
  return n < 16 ? t[n] : n - 16;
}
__host__ __device__ constexpr int n_b(int n) {
  constexpr int t[16] = {0, 1, 0, 0, 0, 1, 0, 0, 0, 1, 0, 1, 0, 1, 0, 1};
  return n < 16 ? t[n] : 0;
}
__host__ __device__ constexpr int item_slot(int it) {
  constexpr int t[16] = {7, 8, 9, 10, 11, 12, 13, 3, 0, 1, 7, 8, 4, 5, 11, 12};
  constexpr int ws[12] = {9, 10, 0, 1, 13, 3, 7, 8, 4, 5, 11, 12};
  return it < 28 ? 7 + it % 7 : (it < 44 ? t[it - 28] : ws[(it - 44) % 12]);
}
__host__ __device__ constexpr int item_wait(int it) {
  constexpr int t[24] = {B_XEMPTY + 6, B_XEMPTY + 7, B_XEMPTY + 7, B_EMPTY + 28, B_EMPTY + 29, B_XEMPTY + 8, B_XEMPTY + 8,
                         B_EMPTY + 32, B_EMPTY + 33,
                         B_EMPTY + 30, B_EMPTY + 31, B_EMPTY + 36, B_EMPTY + 37, B_EMPTY + 34, B_EMPTY + 35, B_EMPTY + 38,
                         B_EMPTY + 39, B_EMPTY + 40, B_EMPTY + 41, B_EMPTY + 42, B_EMPTY + 43};
  return it < 35 ? B_EMPTY + it - 7 : (it < 56 ? t[it - 35] : B_EMPTY + it - 12);
}
__host__ __device__ constexpr int find_item(int kind, int a, int b) {
  for (int n = 0; n < 40; n++)
    if (n_kind(n) == kind && n_a(n) == a && n_b(n) == b) return 28 + n;
  return -1;
}
__host__ __device__ constexpr bool slot_reused(int it) { return it + 12 < NITEMS; }
__host__ __device__ constexpr int w_step(int g) { return g < 4 ? g >> 1 : 2 + ((g - 4) >> 2); }
__host__ __device__ constexpr int w_kq(int g) { return g < 4 ? 2 + (g & 1) : (g - 4) & 3; }

__device__ __forceinline__ int step_atom(int hg, int t) {
  if (t == 6) return min(hg, 6);
  int a = hg < 7 ? hg + 1 + t : 3 + t;
  const int m = hg < 7 ? 7 : 6;
  return a >= m ? a - m : a;
}
template <int OFF, int N>
__device__ __forceinline__ void pack_tile(float (&acc)[128], uint32_t (&p)[16]) {
  acc_fence<OFF, 2 * N>(acc);
#pragma unroll
  for (int i = 0; i < N; i++) p[i] = pack_bf16(acc[OFF + 2 * i], acc[OFF + 2 * i + 1]);
}
template <int OFF>
__device__ __forceinline__ void epi_stash(float (&acc)[128], uint32_t addr) {
  uint32_t p[16];
  pack_tile<OFF, 16>(acc, p);
#pragma unroll
  for (int q = 0; q < 4; q++)
    asm volatile("st.shared.v4.b32 [%0], {%1, %2, %3, %4};" ::"r"(addr + q * 512), "r"(p[4 * q]), "r"(p[4 * q + 1]),
                 "r"(p[4 * q + 2]), "r"(p[4 * q + 3])
                 : "memory");
}
__device__ __forceinline__ void tile_lds(uint32_t (&p)[16], uint32_t addr, uint32_t swp) {
#pragma unroll
  for (int q = 0; q < 4; q++)
    asm volatile("ld.shared.v4.b32 {%0, %1, %2, %3}, [%4];"
                 : "=r"(p[4 * q]), "=r"(p[4 * q + 1]), "=r"(p[4 * q + 2]), "=r"(p[4 * q + 3])
                 : "r"(addr + ((q * 512) ^ swp))
                 : "memory");
}
__device__ __forceinline__ void tile_ldg(uint32_t (&p)[16], const unsigned char* src, uint32_t swp, uint32_t l16) {
  ld_pkt2(src, l16 + swp, &p[0]);
  ld_pkt2(src, l16 + (swp ^ 1024u), &p[8]);
}
template <int OFF, bool ADD>
__device__ __forceinline__ void tile_acc(float (&acc)[128], uint32_t (&p)[16]) {
#pragma unroll
  for (int i = 0; i < 16; i++) {
    acc[OFF + 2 * i] = ADD ? acc[OFF + 2 * i] + bf_lo(p[i]) : bf_lo(p[i]);
    acc[OFF + 2 * i + 1] = ADD ? acc[OFF + 2 * i + 1] + bf_hi(p[i]) : bf_hi(p[i]);
  }
}
template <int OFF>
__device__ __forceinline__ void epi_store(float (&acc)[128], unsigned char* dst, uint32_t par, uint32_t l16) {
  uint32_t p[16];
  pack_tile<OFF, 16>(acc, p);
#pragma unroll
  for (int q = 0; q < 4; q++)
    st_pkt(dst + q * 512, l16, (p[4 * q] & ~1u) | par, p[4 * q + 1], p[4 * q + 2], p[4 * q + 3]);
}
__device__ __forceinline__ void park_sum(float (&acc)[128], uint32_t addr) {
#pragma unroll
  for (int q = 0; q < 4; q++)
    asm volatile("st.shared.v4.f32 [%0], {%1, %2, %3, %4};" ::"r"(addr + q * 512), "f"(acc[64 + 4 * q]),
                 "f"(acc[65 + 4 * q]), "f"(acc[66 + 4 * q]), "f"(acc[67 + 4 * q])
                 : "memory");
}
__device__ __forceinline__ void unpark_sum(float (&acc)[128], uint32_t addr) {
#pragma unroll
  for (int q = 0; q < 4; q++)
    asm volatile("ld.shared.v4.f32 {%0, %1, %2, %3}, [%4];"
                 : "=f"(acc[64 + 4 * q]), "=f"(acc[65 + 4 * q]), "=f"(acc[66 + 4 * q]), "=f"(acc[67 + 4 * q])
                 : "r"(addr + q * 512)
                 : "memory");
}
__device__ __forceinline__ void tile_validate(uint32_t (&p)[16], const unsigned char* src, uint32_t par, uint32_t swp,
                                              uint32_t l16, int tag) {
  int spins = 0;
  while ((((p[0] ^ par) | (p[4] ^ par) | (p[8] ^ par) | (p[12] ^ par)) & 1u) && ++spins < (1 << 20)) {
    tile_ldg(p, src, swp, l16);
  }
  __syncwarp();
}

__global__ void __launch_bounds__(384, 1) fused_attn_kernel(const __grid_constant__ Params prm) {
  extern __shared__ unsigned char smem_raw[];
  const uint32_t sbase = (smem_u32(smem_raw) + 1023) & ~1023u;
  const uint32_t bars = sbase + NSLOT * SLOT;

  const int tid = threadIdx.x;
  const int warp = __shfl_sync(0xffffffffu, tid >> 5, 0), lane = tid & 31;
  const int bid = blockIdx.x;
  const int rb = bid & 7, br = (bid >> 3) & 1, hg = bid >> 4;
  const int grp = br * 8 + rb;
  const CUtensorMap* maps = &prm.maps[br * 5];

  uint32_t pf0 = 0, pf1 = 0;
  if (warp >= 8) {
    asm volatile("setmaxnreg.dec.sync.aligned.u32 24;");
    if (warp != 8) {
      if (warp == 10 && lane == 0) {
        asm volatile("prefetch.tensormap [%0];" ::"l"((uint64_t)(maps + 2)) : "memory");
        asm volatile("prefetch.tensormap [%0];" ::"l"((uint64_t)(maps + 3)) : "memory");
        asm volatile("prefetch.tensormap [%0];" ::"l"((uint64_t)(maps + 4)) : "memory");
      }
      __syncwarp();
      asm volatile("bar.arrive 2, 384;" ::: "memory");
      asm volatile("bar.sync 0, 384;" ::: "memory");
    }
    if (warp == 8) {
      if (lane == 0) {
        TS(2, 0);
        asm volatile("prefetch.tensormap [%0];" ::"l"((uint64_t)(maps + 1)) : "memory");
        asm volatile("prefetch.tensormap [%0];" ::"l"((uint64_t)(maps + 0)) : "memory");
#pragma unroll
        for (int i = 0; i < 14; i++) mbar_init(bars + 8 * i, 1);
      }
      __syncwarp();
      asm volatile("bar.arrive 0, 384;" ::: "memory");
      if (lane == 0) {
#pragma unroll
        for (int i = 0; i < 7; i++) {
          mbar_expect(bars + 8 * (B_FULL + i), SLOT);
          tma_3d(sbase + (7 + i) * SLOT, maps + 1, bars + 8 * (B_FULL + i), 0, 32 * i, 8 * hg + 4);
          if (!(i & 1)) {
            const int k = i >> 1;
            mbar_expect(bars + 8 * (B_XFULL + k), SLOT);
            tma_2d(sbase + xslot(k) * SLOT, maps + 0, bars + 8 * (B_XFULL + k), 64 * k, rb * 128);
          }
          if (i == 0) { TS(2, 1); }
        }
#pragma unroll
        for (int k = 4; k < 7; k++) {
          mbar_expect(bars + 8 * (B_XFULL + k), SLOT);
          tma_2d(sbase + xslot(k) * SLOT, maps + 0, bars + 8 * (B_XFULL + k), 64 * k, rb * 128);
        }
        TS(2, 2);
      }
      __syncwarp();
      asm volatile("bar.sync 2, 384;" ::: "memory");
      if (lane == 0) {
        const int kv0 = br ? 2 * hg : hg, kv1 = br ? 2 * hg + 1 : hg, b0 = rb * 4;
        static_for<7, NITEMS>([&](auto IT) {
          constexpr int it = decltype(IT)::value;
          const uint32_t fb = bars + 8 * (B_FULL + it);
          const uint32_t dst = sbase + item_slot(it) * SLOT;
          if constexpr (it >= 36 && it < 44) {
            if (!br) {
              mbar_arrive(fb);
              return;
            }
          }
          mbar_wait(bars + 8 * item_wait(it));
          mbar_expect(fb, SLOT);
          if constexpr (it < 28) {
            constexpr int hh = it >= 14, pc = it - 14 * hh;
            tma_3d(dst, maps + 1, fb, 0, 32 * pc, 8 * hg + 4 * (1 - hh));
          } else {
            constexpr int kind = n_kind(it - 28), a = n_a(it - 28), b = n_b(it - 28);
            if constexpr (kind == K_V0 || kind == K_V1) {
              tma_5d(dst, maps + 3, fb, 0, 0, b0 + 2 * a, 16 * (kind == K_V1 ? kv1 : kv0), 2 * b);
            } else if constexpr (kind == K_K1) {
              tma_5d(dst, maps + 2, fb, 0, 0, b0 + 2 * a, 2 * b, kv1);
            } else {
              constexpr int step = kind == K_WI ? a >> 1 : w_step(a), kq = kind == K_WI ? a & 1 : w_kq(a);
              tma_2d(dst, maps + 4, fb, 64 * step_atom(hg, step), 512 * hg + 128 * kq);
            }
          }
          if constexpr (it >= 22 && it <= 28 && !(it & 1)) {
            constexpr int j = (it - 22) >> 1;
            mbar_wait(bars + 8 * (B_XEMPTY + j));
            mbar_expect(bars + 8 * (B_KFULL + j), SLOT);
            tma_5d(sbase + xslot(j) * SLOT, maps + 2, bars + 8 * (B_KFULL + j), 0, 0, b0 + 2 * (j & 1), 2 * (j >> 1), kv0);
          }
        });
      }
      __syncwarp();
    } else {
      if (warp >= 10) {
        const int H = br ? 16 : 8;
        const unsigned char* wq = prm.ptr[br * 5 + 3] + hg * 1024;
        const unsigned char* wo = prm.ptr[br * 5 + 4] + (size_t)(hg * 512) * 896;
        auto addr = [&](int b) -> const unsigned char* {
          if (b < 6) {
            int idx = b * 32 + lane;
            if (idx >= 168) idx = 167;
            if (idx < 112) return wq + (size_t)(224 + rb + 8 * (idx >> 2)) * 8192 + (idx & 3) * 256;
            idx -= 112;
            return wq + (size_t)(rb + 8 * (idx >> 1)) * 8192 + (idx & 1) * 256;
          }
          if (b < 22) {
            const int x = b - 6;
            return prm.ptr[br * 5 + 1 + (x >> 3)] + (size_t)((rb * 4 + ((x >> 1) & 3)) * H + (br ? 2 * hg : hg)) * 16384 +
                   (x & 1) * 8192 + lane * 256;
          }
          if (b < 24) return wo + (rb * 32 + lane) * 896 + step_atom(hg, b - 22) * 128;
          if (b < 32) {
            const int x = b - 24;
            return prm.ptr[6 + (x >> 2)] + (size_t)((rb * 4 + (x & 3)) * 16 + 2 * hg + 1) * 16384 + br * 8192 + lane * 256;
          }
          return wo + (min(b - 32, 6) * 8 + rb) * 8192 + lane * 256;
        };
        mbar_wait(bars + 8 * B_FULL);
        uint32_t sink = 0;
#pragma unroll 1
        for (int b = warp - 10; b < 40; b += 4) {
          const unsigned char* p0 = addr(b);
          sink ^= pf0;
          pf0 = ld_pf(p0);
          const unsigned char* p1 = addr(b + 2);
          sink ^= pf1;
          pf1 = ld_pf(p1);
        }
        asm volatile("st.shared.u32 [%0], %1;" ::"r"(bars + 8 * B_SINK), "r"(sink) : "memory");
      }
    }
  } else {
    if (lane == 0) {
#pragma unroll
      for (int i = 0; i < 11; i++) mbar_init(bars + 8 * (14 + 11 * warp + i), 1);
#pragma unroll
      for (int i = 0; i < 9; i++) mbar_init(bars + 8 * (B_EMPTY + 9 * warp + i), 8);
    }
    __syncwarp();
    asm volatile("bar.arrive 2, 384;" ::: "memory");
    asm volatile("bar.sync 0, 384;" ::: "memory");
    asm volatile("setmaxnreg.inc.sync.aligned.u32 240;");
    const int w = warp >> 2;
    float acc[128];
    uint32_t qf0[64], qf1[64];
    uint32_t par;
    asm volatile("ld.relaxed.gpu.global.u32 %0, [%1];" : "=r"(par) : "l"(&g_epoch[bid * 8]) : "memory");
    unsigned char* gbase = g_part + (size_t)grp * GRP_BYTES + warp * TILE;
    const uint32_t l16 = lane * 16;

    if (w == 1) asm volatile("bar.sync 1, 256;" ::: "memory");

    int slot = 0, it = 0;
#pragma unroll
    for (int hh = 0; hh < 2; hh++) {
      {
        if (hh == 0) mbar_wait(bars + 8 * B_XFULL);
        mbar_wait(bars + 8 * (B_FULL + it));
        TSC(hh * 2);
        const uint64_t da = make_desc(sbase + w * 8192, 16, 1024);
        const uint64_t db = make_desc(sbase + (7 + slot) * SLOT, 4096, 1024);
        wg_fence();
        wgmma_ss_n256_init(acc, da, db);
        wgmma_ss_n256(acc, da + 2, db + 128);
        wg_commit();
        it++;
        if (++slot == 7) slot = 0;
      }
#pragma unroll 1
      for (int i = 1; i < 14; i++) {
        const int xs = xslot(i >> 1);
        if (hh == 0 && (i & 1) == 0) mbar_wait(bars + 8 * (B_XFULL + (i >> 1)));
        mbar_wait(bars + 8 * (B_FULL + it));
        const uint64_t da = make_desc(sbase + xs * SLOT + w * 8192 + (i & 1) * 64, 16, 1024);
        const uint64_t db = make_desc(sbase + (7 + slot) * SLOT, 4096, 1024);
        wg_fence();
        wgmma_ss_n256(acc, da, db);
        wgmma_ss_n256(acc, da + 2, db + 128);
        wg_commit();
        if (hh == 0 && i == STAG0 && w == 0) asm volatile("bar.arrive 1, 256;" ::: "memory");
        wg_wait<1>();
        if (lane == 0) {
          mbar_arrive(bars + 8 * (B_EMPTY + it - 1));
          if (hh == 1 && (i & 1) == 0) mbar_arrive(bars + 8 * (B_XEMPTY + (i >> 1) - 1));
        }
        if (hh == 1 && i <= 4 && hg >= 6) st_pkt(gbase + (42 + (hg ^ 1)) * BOX + (i - 1) * 512, l16, par & 1u, 0u, 0u, 0u);
        it++;
        if (++slot == 7) slot = 0;
      }
      wg_wait<0>();
      acc_fence<0, 128>(acc);
      TSC(hh * 2 + 1);
      if (lane == 0) {
        mbar_arrive(bars + 8 * (B_EMPTY + it - 1));
        if (hh == 1) mbar_arrive(bars + 8 * (B_XEMPTY + 6));
      }
#pragma unroll
      for (int i = 0; i < 64; i++) {
        if (hh == 0) qf1[i] = pack_bf16(acc[2 * i], acc[2 * i + 1]);
        else qf0[i] = pack_bf16(acc[2 * i], acc[2 * i + 1]);
      }
    }
    {
      const uint32_t t = qf0[62] & qf0[63] & blockIdx.y;
#pragma unroll
      for (int i = 0; i < 8; i++) qf0[i] ^= t;
    }
    const uint32_t epoch = __shfl_sync(0xffffffffu, par, 0) + 1;
    par = epoch & 1;

    const int jb = (warp >> 1) & 1;
    const uint32_t meta = jb ? 0xEEEEEEEEu : 0x44444444u;
    const uint32_t ustash = sbase + (2 + 4 * w) * SLOT + (warp & 3) * 2048;
#define stash (ustash + l16)
    uint32_t of0[64], of1[64];
    const uint32_t sb16 = (sbase & 0x3FFFF) >> 4;

    auto s_issue = [&](uint32_t(&q)[64], uint32_t bar_a, uint32_t bar_b, uint32_t slot_a, uint32_t slot_b) {
      mbar_wait(bar_a);
      {
        const uint32_t kb = sb16 + slot_a * 1024;
        wg_fence();
        wgmma_rs_n64_init<0, 0, 0x10000>(acc, &q[0], kb);
        static_for<1, 8>([&](auto S) {
          constexpr int s = decltype(S)::value;
          wgmma_rs_n64<0, 0, 0x10000 + (s >> 2) * 512 + (s & 3) * 2>(acc, &q[4 * s], kb);
        });
      }
      mbar_wait(bar_b);
      {
        const uint32_t kb = sb16 + slot_b * 1024;
        wg_fence();
        static_for<0, 8>([&](auto S) {
          constexpr int s = decltype(S)::value;
          wgmma_rs_n64<0, 0, 0x10000 + (s >> 2) * 512 + (s & 3) * 2>(acc, &q[32 + 4 * s], kb);
        });
      }
      wg_commit();
    };
    auto softmax_pv = [&](uint32_t(&o)[64], int ita, int itb, int slot_a, int slot_b, int tsb) {
      uint32_t pf[8];
      float v[16];
#pragma unroll
      for (int i = 0; i < 16; i++) v[i] = jb ? acc[16 + i] : acc[i];
      float m0 = fmaxf(fmaxf(fmaxf(v[0], v[1]), fmaxf(v[4], v[5])), fmaxf(fmaxf(v[8], v[9]), fmaxf(v[12], v[13])));
      float m1 = fmaxf(fmaxf(fmaxf(v[2], v[3]), fmaxf(v[6], v[7])), fmaxf(fmaxf(v[10], v[11]), fmaxf(v[14], v[15])));
      m0 = fmaxf(m0, __shfl_xor_sync(0xffffffffu, m0, 1));
      m1 = fmaxf(m1, __shfl_xor_sync(0xffffffffu, m1, 1));
      m0 = fmaxf(m0, __shfl_xor_sync(0xffffffffu, m0, 2));
      m1 = fmaxf(m1, __shfl_xor_sync(0xffffffffu, m1, 2));
      const float sc = 0.0625f * 1.4426950408889634f;
      const float n0 = -m0 * sc, n1 = -m1 * sc;
#pragma unroll
      for (int jj = 0; jj < 4; jj++) {
        v[4 * jj] = ex2(fmaf(v[4 * jj], sc, n0));
        v[4 * jj + 1] = ex2(fmaf(v[4 * jj + 1], sc, n0));
        v[4 * jj + 2] = ex2(fmaf(v[4 * jj + 2], sc, n1));
        v[4 * jj + 3] = ex2(fmaf(v[4 * jj + 3], sc, n1));
      }
      float s0 = ((v[0] + v[1]) + (v[4] + v[5])) + ((v[8] + v[9]) + (v[12] + v[13]));
      float s1 = ((v[2] + v[3]) + (v[6] + v[7])) + ((v[10] + v[11]) + (v[14] + v[15]));
      s0 += __shfl_xor_sync(0xffffffffu, s0, 1);
      s1 += __shfl_xor_sync(0xffffffffu, s1, 1);
      s0 += __shfl_xor_sync(0xffffffffu, s0, 2);
      s1 += __shfl_xor_sync(0xffffffffu, s1, 2);
      const float r0 = rcp(s0), r1 = rcp(s1);
#pragma unroll
      for (int jj = 0; jj < 4; jj++) {
        pf[2 * jj] = pack_bf16(v[4 * jj] * r0, v[4 * jj + 1] * r0);
        pf[2 * jj + 1] = pack_bf16(v[4 * jj + 2] * r1, v[4 * jj + 3] * r1);
      }
      TSC(tsb + 1);
      mbar_wait(bars + 8 * (B_FULL + ita));
      {
        const uint32_t vb = sb16 + slot_a * 1024;
        wg_fence();
        wgmma_sp_n128_init<0, 0x2000000>(acc, &pf[0], vb, meta);
        wgmma_sp_n128<0, 0x2000000 + 256>(acc, &pf[4], vb, meta);
        wg_commit();
      }
      mbar_wait(bars + 8 * (B_FULL + itb));
      {
        const uint32_t vb = sb16 + slot_b * 1024;
        wg_fence();
        wgmma_sp_n128_init<64, 0x2000000>(acc, &pf[0], vb, meta);
        wgmma_sp_n128<64, 0x2000000 + 256>(acc, &pf[4], vb, meta);
      }
      wg_commit();
      wg_wait<1>();
      acc_fence<0, 64>(acc);
#pragma unroll
      for (int i = 0; i < 32; i++) o[i] = pack_bf16(acc[2 * i], acc[2 * i + 1]);
#pragma unroll
      for (int i = 0; i < 32; i++) asm volatile("" : "+r"(o[i])::"memory");
      wg_wait<0>();
      acc_fence<64, 64>(acc);
      TSC(tsb + 2);
      if (lane == 0) {
        mbar_arrive2(bars + 8 * (B_EMPTY + ita));
        mbar_arrive2(bars + 8 * (B_EMPTY + itb));
      }
#pragma unroll
      for (int i = 32; i < 64; i++) o[i] = pack_bf16(acc[2 * i], acc[2 * i + 1]);
    };
#define SEL_IT(kind, b) (w ? find_item(kind, 1, b) : find_item(kind, 0, b))
#define SEL_SLOT(kind, b) (w ? item_slot(find_item(kind, 1, b)) : item_slot(find_item(kind, 0, b)))

    s_issue(qf0, bars + 8 * (B_KFULL + w), bars + 8 * (B_KFULL + 2 + w), 4 * w, 4 * w + 1);
    wg_wait<0>();
    acc_fence<0, 32>(acc);
    TSC(4);
    if (lane == 0) mbar_arrive2(bars + 8 * (B_XEMPTY + 7 + w));
    softmax_pv(qf0, SEL_IT(K_V0, 0), SEL_IT(K_V0, 1), SEL_SLOT(K_V0, 0), SEL_SLOT(K_V0, 1), 4);

    static_for<0, 4>([&](auto G) {
      constexpr int g = decltype(G)::value, c = g >> 1, kq = g & 1, it2 = find_item(K_WI, g, 0);
      mbar_wait(bars + 8 * (B_FULL + it2));
      wg_fence();
      g2_group<32 * (c & 1), kq == 0, 0x2000000 + item_slot(it2) * 1024>(acc, &qf0[32 * kq], sb16);
      wg_commit();
      if constexpr (g > 0) {
        wg_wait<1>();
        if (lane == 0) mbar_arrive(bars + 8 * (B_EMPTY + find_item(K_WI, g - 1, 0)));
      }
      if constexpr (g == 2) {
        mbar_wait(bars + 8 * (B_XEMPTY + 4 + w));
        epi_stash<0>(acc, stash);
      }
    });
    s_issue(qf1, bars + 8 * (B_FULL + SEL_IT(K_K1, 0)), bars + 8 * (B_FULL + SEL_IT(K_K1, 1)), SEL_SLOT(K_K1, 0),
            SEL_SLOT(K_K1, 1));
    wg_wait<1>();
    TSC(7);
    if (lane == 0) mbar_arrive(bars + 8 * (B_EMPTY + find_item(K_WI, 3, 0)));
    epi_stash<32>(acc, stash + 8192);
    wg_wait<0>();
    acc_fence<0, 32>(acc);
    TSC(12);
    if (lane == 0) {
      mbar_arrive2(bars + 8 * (B_EMPTY + SEL_IT(K_K1, 0)));
      mbar_arrive2(bars + 8 * (B_EMPTY + SEL_IT(K_K1, 1)));
    }
    {
      const uint32_t z = blockIdx.y;
#pragma unroll
      for (int i = 0; i < 64; i++) of0[i] = qf0[i] ^ z;
    }
    softmax_pv(of1, SEL_IT(K_V1, 0), SEL_IT(K_V1, 1), SEL_SLOT(K_V1, 0), SEL_SLOT(K_V1, 1), 12);

    const unsigned char* inbox = gbase + min(hg, 6) * (6 * BOX);
    const unsigned char* inbox_x = gbase + (42 + hg) * BOX;
    const uint32_t swp = hg == 6 ? 1024u : 0u;
    const uint32_t ibar = bars + 8 * (B_INB + 2 * warp);
    uint32_t pk[16];
    auto fetch = [&](int u) {
      asm volatile("fence.proxy.async.shared::cta;" ::: "memory");
      __syncwarp();
      if (lane == 0) {
        mbar_expect(ibar + 8 * (u & 1), TILE);
        asm volatile("cp.async.bulk.shared::cluster.global.mbarrier::complete_tx::bytes [%0], [%1], %2, [%3];" ::"r"(
                         ustash + (u & 1) * 8192),
                     "l"(inbox + u * BOX), "n"(TILE), "r"(ibar + 8 * (u & 1))
                     : "memory");
      }
    };
    auto take = [&](int u) {
      mbar_wait_phase(ibar + 8 * (u & 1), (u >> 1) & 1);
      tile_lds(pk, stash + (u & 1) * 8192, swp);
      tile_validate(pk, inbox + u * BOX, par, swp, l16, u);
    };
    auto send = [&](auto T) {
      constexpr int t = decltype(T)::value;
      TSC(15 + t);
      const int a = step_atom(hg, t);
      epi_store<32 * (t & 1)>(acc, gbase + (hg < 7 ? a * 6 + t : 42 + a) * BOX, par, l16);
      if constexpr (t == 2) { fetch(0); fetch(1); }
      if constexpr (t > 2) fetch(t - 1);
    };
    tile_lds(pk, stash, 0);
    tile_acc<0, false>(acc, pk);
    static_for<0, 20>([&](auto G) {
      constexpr int g = decltype(G)::value, s = w_step(g), kq = w_kq(g), it2 = find_item(K_W, g, 0);
      mbar_wait(bars + 8 * (B_FULL + it2));
      wg_fence();
      g2_group<32 * (s & 1), kq == 0, 0x2000000 + item_slot(it2) * 1024>(
          acc, kq < 2 ? &of0[32 * (kq & 1)] : &of1[32 * (kq & 1)], sb16);
      wg_commit();
      if constexpr (g > 0) {
        wg_wait<1>();
        if constexpr (slot_reused(find_item(K_W, g - 1, 0)))
          if (lane == 0) mbar_arrive(bars + 8 * (B_EMPTY + find_item(K_W, g - 1, 0)));
        if constexpr (w_step(g - 1) != s) send(IC<s - 1>{});
      }
      if constexpr (g == 0) {
        tile_lds(pk, stash + 8192, 0);
        tile_acc<32, false>(acc, pk);
      }
      if constexpr (s == 3 && kq == 2) { take(0); tile_acc<64, false>(acc, pk); }
      if constexpr (s >= 3 && kq == 3) {
        if constexpr (s > 3) unpark_sum(acc, stash + ((s - 3) & 1) * 8192);
        take(s - 2);
        tile_acc<64, true>(acc, pk);
        park_sum(acc, stash + ((s - 2) & 1) * 8192);
      }
    });
    {
      const uint32_t sa = sb16 + (swp >> 8), sb = sb16 + 4 - (swp >> 8);
      static_for<0, 4>([&](auto KQ) {
        constexpr int kq = decltype(KQ)::value, it2 = find_item(K_W, 20 + kq, 0);
        mbar_wait(bars + 8 * (B_FULL + it2));
        wg_fence();
        g2_group32<0, kq == 0, 0x2000000 + item_slot(it2) * 1024>(acc, kq < 2 ? &of0[32 * (kq & 1)] : &of1[32 * (kq & 1)], sa);
        if constexpr (kq == 1) {
          wg_commit();
          wg_wait<1>();
          send(IC<5>{});
        }
      });
      wg_commit();
      wg_fence();
      static_for<0, 4>([&](auto KQ) {
        constexpr int kq = decltype(KQ)::value, it2 = find_item(K_W, 20 + kq, 0);
        g2_group32<16, kq == 0, 0x2000000 + item_slot(it2) * 1024>(acc, kq < 2 ? &of0[32 * (kq & 1)] : &of1[32 * (kq & 1)], sb);
      });
      wg_commit();
      wg_wait<1>();
      TSC(21);
      if (hg >= 6) {
        uint32_t p[16];
        pack_tile<0, 8>(acc, p);
        unsigned char* dst = gbase + (42 + (hg ^ 1)) * BOX;
        st_pkt(dst + swp, l16, (p[0] & ~1u) | par, p[1], p[2], p[3]);
        st_pkt(dst + swp + 512, l16, (p[4] & ~1u) | par, p[5], p[6], p[7]);
        st_pkt(dst + (swp ^ 1024u), l16, par, 0u, 0u, 0u);
        st_pkt(dst + (swp ^ 1024u) + 512, l16, par, 0u, 0u, 0u);
      }
      unpark_sum(acc, stash + 8192);
      acc_fence<0, 16>(acc);
#pragma unroll
      for (int i = 0; i < 16; i++) acc[64 + i] += acc[i];
      take(4);
      tile_acc<64, true>(acc, pk);
      uint32_t pl[16];
      tile_ldg(pk, inbox + 5 * BOX, swp, l16);
      tile_ldg(pl, inbox_x, swp, l16);
      tile_validate(pk, inbox + 5 * BOX, par, swp, l16, 5);
      tile_acc<64, true>(acc, pk);
      tile_validate(pl, inbox_x, par, swp, l16, 6);
      tile_acc<64, true>(acc, pl);
      __nv_bfloat16* o = prm.out + (size_t)(rb * 128 + warp * 16 + (lane >> 2)) * 896 + br * 448 + 64 * min(hg, 6) +
                         2 * (lane & 3);
      if (hg < 6) {
#pragma unroll
        for (int j = 0; j < 4; j++) {
          *reinterpret_cast<uint32_t*>(o + 8 * j) = pack_bf16(acc[64 + 4 * j], acc[65 + 4 * j]);
          *reinterpret_cast<uint32_t*>(o + 8 * 896 + 8 * j) = pack_bf16(acc[66 + 4 * j], acc[67 + 4 * j]);
        }
      }
      wg_wait<0>();
      TSC(22);
      acc_fence<16, 16>(acc);
      __nv_bfloat16* ob = o + (hg == 6 ? 0 : 32);
#pragma unroll
      for (int j = 0; j < 4; j++) {
        *reinterpret_cast<uint32_t*>(ob + 8 * j) =
            pack_bf16(acc[80 + 4 * j] + acc[16 + 4 * j], acc[81 + 4 * j] + acc[17 + 4 * j]);
        *reinterpret_cast<uint32_t*>(ob + 8 * 896 + 8 * j) =
            pack_bf16(acc[82 + 4 * j] + acc[18 + 4 * j], acc[83 + 4 * j] + acc[19 + 4 * j]);
      }
    }
    TSC(23);
    if (tid == 0) g_epoch[bid * 8] = epoch;
  }
}

typedef CUresult (*EncodeFn)(CUtensorMap*, CUtensorMapDataType, cuuint32_t, void*, const cuuint64_t*, const cuuint64_t*,
                             const cuuint32_t*, const cuuint32_t*, CUtensorMapInterleave, CUtensorMapSwizzle,
                             CUtensorMapL2promotion, CUtensorMapFloatOOBfill);

void encode(EncodeFn fn, CUtensorMap* m, int rank, const void* ptr, const cuuint64_t* dims, const cuuint64_t* strides,
            const cuuint32_t* box) {
  cuuint32_t es[5] = {1, 1, 1, 1, 1};
  fn(m, CU_TENSOR_MAP_DATA_TYPE_BFLOAT16, rank, const_cast<void*>(ptr), dims, strides, box, es,
     CU_TENSOR_MAP_INTERLEAVE_NONE, CU_TENSOR_MAP_SWIZZLE_128B, CU_TENSOR_MAP_L2_PROMOTION_L2_256B,
     CU_TENSOR_MAP_FLOAT_OOB_FILL_NONE);
}

}

extern "C" void kernel_launch(void* const* d_in, const int* in_sizes, int n_in, void* d_out, int out_size) {
  (void)in_sizes; (void)n_in; (void)out_size;
  void* fnp = nullptr;
  cudaDriverEntryPointQueryResult qr;
  cudaGetDriverEntryPoint("cuTensorMapEncodeTiled", &fnp, cudaEnableDefault, &qr);
  EncodeFn fn = (EncodeFn)fnp;
  Params prm;
  for (int br = 0; br < 2; br++) {
    const void* x = d_in[br * 5 + 0];
    const void* kc = d_in[br * 5 + 1];
    const void* vc = d_in[br * 5 + 2];
    const void* wq = d_in[br * 5 + 3];
    const void* wo = d_in[br * 5 + 4];
    const cuuint64_t H = br ? 16 : 8;
    {
      cuuint64_t dims[2] = {448, 1024}, str[1] = {896};
      cuuint32_t box[2] = {64, 128};
      encode(fn, &prm.maps[br * 5 + 0], 2, x, dims, str, box);
    }
    {
      cuuint64_t dims[3] = {64, 448, 64}, str[2] = {8192, 128};
      cuuint32_t box[3] = {64, 32, 4};
      encode(fn, &prm.maps[br * 5 + 1], 3, wq, dims, str, box);
    }
    {
      cuuint64_t dims[5] = {64, 32, 32, 4, H}, str[4] = {512, H * 16384, 128, 16384};
      cuuint32_t box[5] = {64, 32, 2, 2, 1};
      encode(fn, &prm.maps[br * 5 + 2], 5, kc, dims, str, box);
    }
    {
      cuuint64_t dims[5] = {64, 2, 32, 16 * H, 4}, str[4] = {512, H * 16384, 1024, 128};
      cuuint32_t box[5] = {64, 2, 2, 16, 2};
      encode(fn, &prm.maps[br * 5 + 3], 5, vc, dims, str, box);
    }
    {
      cuuint64_t dims[2] = {448, 4096}, str[1] = {896};
      cuuint32_t box[2] = {64, 128};
      encode(fn, &prm.maps[br * 5 + 4], 2, wo, dims, str, box);
    }
  }
  for (int i = 0; i < 10; i++) prm.ptr[i] = (const unsigned char*)d_in[i];
  prm.out = (__nv_bfloat16*)d_out;
  cudaFuncSetAttribute(fused_attn_kernel, cudaFuncAttributeMaxDynamicSharedMemorySize, SMEM_BYTES);
  fused_attn_kernel<<<128, 384, SMEM_BYTES>>>(prm);
}
```

```cpp
#include <cuda_runtime.h>
#include <cuda_bf16.h>
#include <cuda.h>
#include <stdint.h>

namespace {

#define STAG0 0
#define RED_LAG 1
#define RED5_AT 1
#define WO_BY_STEP 0
#define LAG2 0
#define TAIL_LD 1
#define HSWAP 0
#define WO_EARLY 0
#define FLAG 2
#define ASK_KQ 2
#define PP0 3
#define PP_AT 4
#define TAILV 1
#define ASK4 3
#define FOLD4_LATE 1
#define TAIL_LDX 2
#define OUT64 2
#define PFW 2
#define PFD 2
#define PF_BURST 0
#define SPRINT 4
#define PREW5 0
#define POLL_NS 50
#define PF_SWITCH 24
#define PREW_N 0

#define PROF_SMEM 0
constexpr int SLOT = 16384;
constexpr int NSLOT = 14;
constexpr int NITEMS = 68;
constexpr int B_XFULL = 0;
constexpr int B_FULL = 7;
constexpr int B_KFULL = 79;
constexpr int B_INB = 83;
constexpr int B_EMPTY = 102;
constexpr int B_XEMPTY = 165;
constexpr int B_GATE = 174;
constexpr int B_SINK = 184;
constexpr int NBAR = 185;
constexpr int SMEM_BYTES = 1024 + NSLOT * SLOT + NBAR * 8 + PROF_SMEM;
constexpr int TILE = 2048;
constexpr int BOX = 8 * TILE;
constexpr int GRP_BYTES = 49 * BOX;

struct Params {
  CUtensorMap maps[10];
  const unsigned char* ptr[10];
  __nv_bfloat16* out;
};

__device__ __align__(1024) unsigned char g_part[16 * GRP_BYTES];
__device__ unsigned int g_epoch[128 * 8];

#define TS(role, idx)
#define TSC(idx)

__device__ __forceinline__ uint32_t smem_u32(const void* p) { return (uint32_t)__cvta_generic_to_shared(p); }
__device__ __forceinline__ void mbar_init(uint32_t a, uint32_t c) {
  asm volatile("mbarrier.init.shared::cta.b64 [%0], %1;" ::"r"(a), "r"(c) : "memory");
}
__device__ __forceinline__ void mbar_expect(uint32_t a, uint32_t b) {
  asm volatile("mbarrier.arrive.expect_tx.shared::cta.b64 _, [%0], %1;" ::"r"(a), "r"(b) : "memory");
}
__device__ __forceinline__ void mbar_arrive(uint32_t a) {
  asm volatile("mbarrier.arrive.shared::cta.b64 _, [%0];" ::"r"(a) : "memory");
}
__device__ __forceinline__ void mbar_arrive2(uint32_t a) {
  asm volatile("mbarrier.arrive.shared::cta.b64 _, [%0], 2;" ::"r"(a) : "memory");
}
__device__ __forceinline__ void mbar_wait(uint32_t a) {
  asm volatile(
      "{\n.reg .pred P;\n.reg .u32 n;\nmov.u32 n, 0;\n"
      "LW:\nmbarrier.try_wait.parity.shared::cta.b64 P, [%0], 0;\n"
      "@P bra LD;\nadd.u32 n, n, 1;\nsetp.lt.u32 P, n, 0x400000;\n@P bra LW;\n"
      "LD:\n}" ::"r"(a)
      : "memory");
}
__device__ __forceinline__ void mbar_wait_phase(uint32_t a, uint32_t parity) {
  asm volatile(
      "{\n.reg .pred P;\n.reg .u32 n;\nmov.u32 n, 0;\n"
      "LW:\nmbarrier.try_wait.parity.shared::cta.b64 P, [%0], %1;\n"
      "@P bra LD;\nadd.u32 n, n, 1;\nsetp.lt.u32 P, n, 0x400000;\n@P bra LW;\n"
      "LD:\n}" ::"r"(a),
      "r"(parity)
      : "memory");
}
__device__ __forceinline__ void tma_2d(uint32_t dst, const CUtensorMap* m, uint32_t bar, int c0, int c1) {
  asm volatile(
      "cp.async.bulk.tensor.2d.shared::cluster.global.mbarrier::complete_tx::bytes [%0], [%1, {%3, %4}], [%2];" ::"r"(dst),
      "l"((uint64_t)m), "r"(bar), "r"(c0), "r"(c1)
      : "memory");
}
__device__ __forceinline__ void tma_3d(uint32_t dst, const CUtensorMap* m, uint32_t bar, int c0, int c1, int c2) {
  asm volatile(
      "cp.async.bulk.tensor.3d.shared::cluster.global.mbarrier::complete_tx::bytes [%0], [%1, {%3, %4, %5}], [%2];" ::"r"(
          dst),
      "l"((uint64_t)m), "r"(bar), "r"(c0), "r"(c1), "r"(c2)
      : "memory");
}
__device__ __forceinline__ void tma_5d(uint32_t dst, const CUtensorMap* m, uint32_t bar, int c0, int c1, int c2, int c3,
                                       int c4) {
  asm volatile(
      "cp.async.bulk.tensor.5d.shared::cluster.global.mbarrier::complete_tx::bytes [%0], [%1, {%3, %4, %5, %6, %7}], "
      "[%2];" ::"r"(dst),
      "l"((uint64_t)m), "r"(bar), "r"(c0), "r"(c1), "r"(c2), "r"(c3), "r"(c4)
      : "memory");
}
__device__ __forceinline__ uint32_t ld_pf(const void* p) {
  uint32_t v;
  asm volatile("ld.global.cg.L2::256B.u32 %0, [%1];" : "=r"(v) : "l"(p));
  return v;
}
__device__ __forceinline__ void wg_fence() { asm volatile("wgmma.fence.sync.aligned;" ::: "memory"); }
__device__ __forceinline__ void wg_commit() { asm volatile("wgmma.commit_group.sync.aligned;" ::: "memory"); }
template <int N>
__device__ __forceinline__ void wg_wait() {
  asm volatile("wgmma.wait_group.sync.aligned %0;" ::"n"(N) : "memory");
}
template <int OFF, int N>
__device__ __forceinline__ void acc_fence(float (&d)[128]) {
#pragma unroll
  for (int i = 0; i < N; i++) asm volatile("" : "+f"(d[OFF + i])::"memory");
}
__device__ __forceinline__ uint32_t pack_bf16(float lo, float hi) {
  uint32_t r;
  asm("cvt.rn.bf16x2.f32 %0, %1, %2;" : "=r"(r) : "f"(hi), "f"(lo));
  return r;
}
__device__ __forceinline__ float bf_lo(uint32_t v) { return __uint_as_float(v << 16); }
__device__ __forceinline__ float bf_hi(uint32_t v) { return __uint_as_float(v & 0xffff0000u); }
__device__ __forceinline__ float ex2(float x) {
  float r;
  asm("ex2.approx.ftz.f32 %0, %1;" : "=f"(r) : "f"(x));
  return r;
}
__device__ __forceinline__ float rcp(float x) {
  float r;
  asm("rcp.approx.ftz.f32 %0, %1;" : "=f"(r) : "f"(x));
  return r;
}
__device__ __forceinline__ void st_pkt(const void* p, uint32_t off, uint32_t a, uint32_t b, uint32_t c, uint32_t d) {
  asm volatile(
      "{\n.reg .b64 lo, hi, ad;\n.reg .b128 v;\nmov.b64 lo, {%2, %3};\nmov.b64 hi, {%4, %5};\nmov.b128 v, {lo, hi};\n"
      "cvt.u64.u32 ad, %1;\nadd.u64 ad, ad, %0;\nst.relaxed.gpu.global.b128 [ad], v;\n}" ::"l"(p),
      "r"(off), "r"(a), "r"(b), "r"(c), "r"(d)
      : "memory");
}
__device__ __forceinline__ void ld_pkt2(const void* p, uint32_t off, uint32_t* v) {
  asm volatile(
      "{\n.reg .b64 lo, hi, ad;\n.reg .b128 v, w;\ncvt.u64.u32 ad, %9;\nadd.u64 ad, ad, %8;\n"
      "ld.relaxed.gpu.global.b128 v, [ad];\nld.relaxed.gpu.global.b128 w, [ad+512];\n"
      "mov.b128 {lo, hi}, v;\nmov.b64 {%0, %1}, lo;\nmov.b64 {%2, %3}, hi;\n"
      "mov.b128 {lo, hi}, w;\nmov.b64 {%4, %5}, lo;\nmov.b64 {%6, %7}, hi;\n}"
      : "=r"(v[0]), "=r"(v[1]), "=r"(v[2]), "=r"(v[3]), "=r"(v[4]), "=r"(v[5]), "=r"(v[6]), "=r"(v[7])
      : "l"(p), "r"(off)
      : "memory");
}
__device__ __forceinline__ uint64_t make_desc(uint32_t addr, uint32_t lbo, uint32_t sbo) {
  return (uint64_t)((addr & 0x3FFFF) >> 4) | ((uint64_t)(lbo >> 4) << 16) | ((uint64_t)(sbo >> 4) << 32) |
         ((uint64_t)1 << 62);
}

__device__ __forceinline__ void wgmma_ss_n256(float (&d)[128], uint64_t da, uint64_t db) {
  asm volatile(
    "wgmma.mma_async.sync.aligned.m64n256k16.f32.bf16.bf16 {%0, %1, %2, %3, %4, %5, %6, %7, %8, %9, %10, %11, %12, %13, %14, %15, %16, %17, %18, %19, %20, %21, %22, %23, %24, %25, %26, %27, %28, %29, %30, %31, %32, %33, %34, %35, %36, %37, %38, %39, %40, %41, %42, %43, %44, %45, %46, %47, %48, %49, %50, %51, %52, %53, %54, %55, %56, %57, %58, %59, %60, %61, %62, %63, %64, %65, %66, %67, %68, %69, %70, %71, %72, %73, %74, %75, %76, %77, %78, %79, %80, %81, %82, %83, %84, %85, %86, %87, %88, %89, %90, %91, %92, %93, %94, %95, %96, %97, %98, %99, %100, %101, %102, %103, %104, %105, %106, %107, %108, %109, %110, %111, %112, %113, %114, %115, %116, %117, %118, %119, %120, %121, %122, %123, %124, %125, %126, %127}, %128, %129, 1, 1, 1, 0, 1;\n"
    : "+f"(d[0]), "+f"(d[1]), "+f"(d[2]), "+f"(d[3]), "+f"(d[4]), "+f"(d[5]), "+f"(d[6]), "+f"(d[7]), "+f"(d[8]), "+f"(d[9]), "+f"(d[10]), "+f"(d[11]), "+f"(d[12]), "+f"(d[13]), "+f"(d[14]), "+f"(d[15]), "+f"(d[16]), "+f"(d[17]), "+f"(d[18]), "+f"(d[19]), "+f"(d[20]), "+f"(d[21]), "+f"(d[22]), "+f"(d[23]), "+f"(d[24]), "+f"(d[25]), "+f"(d[26]), "+f"(d[27]), "+f"(d[28]), "+f"(d[29]), "+f"(d[30]), "+f"(d[31]), "+f"(d[32]), "+f"(d[33]), "+f"(d[34]), "+f"(d[35]), "+f"(d[36]), "+f"(d[37]), "+f"(d[38]), "+f"(d[39]), "+f"(d[40]), "+f"(d[41]), "+f"(d[42]), "+f"(d[43]), "+f"(d[44]), "+f"(d[45]), "+f"(d[46]), "+f"(d[47]), "+f"(d[48]), "+f"(d[49]), "+f"(d[50]), "+f"(d[51]), "+f"(d[52]), "+f"(d[53]), "+f"(d[54]), "+f"(d[55]), "+f"(d[56]), "+f"(d[57]), "+f"(d[58]), "+f"(d[59]), "+f"(d[60]), "+f"(d[61]), "+f"(d[62]), "+f"(d[63]), "+f"(d[64]), "+f"(d[65]), "+f"(d[66]), "+f"(d[67]), "+f"(d[68]), "+f"(d[69]), "+f"(d[70]), "+f"(d[71]), "+f"(d[72]), "+f"(d[73]), "+f"(d[74]), "+f"(d[75]), "+f"(d[76]), "+f"(d[77]), "+f"(d[78]), "+f"(d[79]), "+f"(d[80]), "+f"(d[81]), "+f"(d[82]), "+f"(d[83]), "+f"(d[84]), "+f"(d[85]), "+f"(d[86]), "+f"(d[87]), "+f"(d[88]), "+f"(d[89]), "+f"(d[90]), "+f"(d[91]), "+f"(d[92]), "+f"(d[93]), "+f"(d[94]), "+f"(d[95]), "+f"(d[96]), "+f"(d[97]), "+f"(d[98]), "+f"(d[99]), "+f"(d[100]), "+f"(d[101]), "+f"(d[102]), "+f"(d[103]), "+f"(d[104]), "+f"(d[105]), "+f"(d[106]), "+f"(d[107]), "+f"(d[108]), "+f"(d[109]), "+f"(d[110]), "+f"(d[111]), "+f"(d[112]), "+f"(d[113]), "+f"(d[114]), "+f"(d[115]), "+f"(d[116]), "+f"(d[117]), "+f"(d[118]), "+f"(d[119]), "+f"(d[120]), "+f"(d[121]), "+f"(d[122]), "+f"(d[123]), "+f"(d[124]), "+f"(d[125]), "+f"(d[126]), "+f"(d[127])
    : "l"(da), "l"(db));
}

template <int OFF, int IMM>
__device__ __forceinline__ void wgmma_sp_n128(float (&d)[128], const uint32_t* a, uint32_t base, uint32_t meta) {
  asm volatile(
    "{\n.reg .b32 lo;\n.reg .b64 db;\nadd.u32 lo, %68, %70;\nmov.b64 db, {lo, 0x40000040};\n"
    "wgmma.mma_async.sp.sync.aligned.m64n128k32.f32.bf16.bf16 {%0, %1, %2, %3, %4, %5, %6, %7, %8, %9, %10, %11, %12, %13, %14, %15, %16, %17, %18, %19, %20, %21, %22, %23, %24, %25, %26, %27, %28, %29, %30, %31, %32, %33, %34, %35, %36, %37, %38, %39, %40, %41, %42, %43, %44, %45, %46, %47, %48, %49, %50, %51, %52, %53, %54, %55, %56, %57, %58, %59, %60, %61, %62, %63}, {%64, %65, %66, %67}, db, %69, 0, 1, 1, 1, 1;\n}\n"
    : "+f"(d[OFF + 0]), "+f"(d[OFF + 1]), "+f"(d[OFF + 2]), "+f"(d[OFF + 3]), "+f"(d[OFF + 4]), "+f"(d[OFF + 5]), "+f"(d[OFF + 6]), "+f"(d[OFF + 7]), "+f"(d[OFF + 8]), "+f"(d[OFF + 9]), "+f"(d[OFF + 10]), "+f"(d[OFF + 11]), "+f"(d[OFF + 12]), "+f"(d[OFF + 13]), "+f"(d[OFF + 14]), "+f"(d[OFF + 15]), "+f"(d[OFF + 16]), "+f"(d[OFF + 17]), "+f"(d[OFF + 18]), "+f"(d[OFF + 19]), "+f"(d[OFF + 20]), "+f"(d[OFF + 21]), "+f"(d[OFF + 22]), "+f"(d[OFF + 23]), "+f"(d[OFF + 24]), "+f"(d[OFF + 25]), "+f"(d[OFF + 26]), "+f"(d[OFF + 27]), "+f"(d[OFF + 28]), "+f"(d[OFF + 29]), "+f"(d[OFF + 30]), "+f"(d[OFF + 31]), "+f"(d[OFF + 32]), "+f"(d[OFF + 33]), "+f"(d[OFF + 34]), "+f"(d[OFF + 35]), "+f"(d[OFF + 36]), "+f"(d[OFF + 37]), "+f"(d[OFF + 38]), "+f"(d[OFF + 39]), "+f"(d[OFF + 40]), "+f"(d[OFF + 41]), "+f"(d[OFF + 42]), "+f"(d[OFF + 43]), "+f"(d[OFF + 44]), "+f"(d[OFF + 45]), "+f"(d[OFF + 46]), "+f"(d[OFF + 47]), "+f"(d[OFF + 48]), "+f"(d[OFF + 49]), "+f"(d[OFF + 50]), "+f"(d[OFF + 51]), "+f"(d[OFF + 52]), "+f"(d[OFF + 53]), "+f"(d[OFF + 54]), "+f"(d[OFF + 55]), "+f"(d[OFF + 56]), "+f"(d[OFF + 57]), "+f"(d[OFF + 58]), "+f"(d[OFF + 59]), "+f"(d[OFF + 60]), "+f"(d[OFF + 61]), "+f"(d[OFF + 62]), "+f"(d[OFF + 63])
    : "r"(a[0]), "r"(a[1]), "r"(a[2]), "r"(a[3]), "r"(base), "r"(meta), "n"(IMM));
}

template <int TB, int OFF, int IMM>
__device__ __forceinline__ void wgmma_rs_n64(float (&d)[128], const uint32_t* a, uint32_t base) {
  asm volatile(
    "{\n.reg .b32 lo;\n.reg .b64 db;\nadd.u32 lo, %36, %38;\nmov.b64 db, {lo, 0x40000040};\n"
    "wgmma.mma_async.sync.aligned.m64n64k16.f32.bf16.bf16 {%0, %1, %2, %3, %4, %5, %6, %7, %8, %9, %10, %11, %12, %13, %14, %15, %16, %17, %18, %19, %20, %21, %22, %23, %24, %25, %26, %27, %28, %29, %30, %31}, {%32, %33, %34, %35}, db, 1, 1, 1, %37;\n}\n"
    : "+f"(d[OFF + 0]), "+f"(d[OFF + 1]), "+f"(d[OFF + 2]), "+f"(d[OFF + 3]), "+f"(d[OFF + 4]), "+f"(d[OFF + 5]), "+f"(d[OFF + 6]), "+f"(d[OFF + 7]), "+f"(d[OFF + 8]), "+f"(d[OFF + 9]), "+f"(d[OFF + 10]), "+f"(d[OFF + 11]), "+f"(d[OFF + 12]), "+f"(d[OFF + 13]), "+f"(d[OFF + 14]), "+f"(d[OFF + 15]), "+f"(d[OFF + 16]), "+f"(d[OFF + 17]), "+f"(d[OFF + 18]), "+f"(d[OFF + 19]), "+f"(d[OFF + 20]), "+f"(d[OFF + 21]), "+f"(d[OFF + 22]), "+f"(d[OFF + 23]), "+f"(d[OFF + 24]), "+f"(d[OFF + 25]), "+f"(d[OFF + 26]), "+f"(d[OFF + 27]), "+f"(d[OFF + 28]), "+f"(d[OFF + 29]), "+f"(d[OFF + 30]), "+f"(d[OFF + 31])
    : "r"(a[0]), "r"(a[1]), "r"(a[2]), "r"(a[3]), "r"(base), "n"(TB), "n"(IMM));
}

__device__ __forceinline__ void wgmma_ss_n256_init(float (&d)[128], uint64_t da, uint64_t db) {
  asm volatile(
    "wgmma.mma_async.sync.aligned.m64n256k16.f32.bf16.bf16 {%0, %1, %2, %3, %4, %5, %6, %7, %8, %9, %10, %11, %12, %13, %14, %15, %16, %17, %18, %19, %20, %21, %22, %23, %24, %25, %26, %27, %28, %29, %30, %31, %32, %33, %34, %35, %36, %37, %38, %39, %40, %41, %42, %43, %44, %45, %46, %47, %48, %49, %50, %51, %52, %53, %54, %55, %56, %57, %58, %59, %60, %61, %62, %63, %64, %65, %66, %67, %68, %69, %70, %71, %72, %73, %74, %75, %76, %77, %78, %79, %80, %81, %82, %83, %84, %85, %86, %87, %88, %89, %90, %91, %92, %93, %94, %95, %96, %97, %98, %99, %100, %101, %102, %103, %104, %105, %106, %107, %108, %109, %110, %111, %112, %113, %114, %115, %116, %117, %118, %119, %120, %121, %122, %123, %124, %125, %126, %127}, %128, %129, 0, 1, 1, 0, 1;\n"
    : "=f"(d[0]), "=f"(d[1]), "=f"(d[2]), "=f"(d[3]), "=f"(d[4]), "=f"(d[5]), "=f"(d[6]), "=f"(d[7]), "=f"(d[8]), "=f"(d[9]), "=f"(d[10]), "=f"(d[11]), "=f"(d[12]), "=f"(d[13]), "=f"(d[14]), "=f"(d[15]), "=f"(d[16]), "=f"(d[17]), "=f"(d[18]), "=f"(d[19]), "=f"(d[20]), "=f"(d[21]), "=f"(d[22]), "=f"(d[23]), "=f"(d[24]), "=f"(d[25]), "=f"(d[26]), "=f"(d[27]), "=f"(d[28]), "=f"(d[29]), "=f"(d[30]), "=f"(d[31]), "=f"(d[32]), "=f"(d[33]), "=f"(d[34]), "=f"(d[35]), "=f"(d[36]), "=f"(d[37]), "=f"(d[38]), "=f"(d[39]), "=f"(d[40]), "=f"(d[41]), "=f"(d[42]), "=f"(d[43]), "=f"(d[44]), "=f"(d[45]), "=f"(d[46]), "=f"(d[47]), "=f"(d[48]), "=f"(d[49]), "=f"(d[50]), "=f"(d[51]), "=f"(d[52]), "=f"(d[53]), "=f"(d[54]), "=f"(d[55]), "=f"(d[56]), "=f"(d[57]), "=f"(d[58]), "=f"(d[59]), "=f"(d[60]), "=f"(d[61]), "=f"(d[62]), "=f"(d[63]), "=f"(d[64]), "=f"(d[65]), "=f"(d[66]), "=f"(d[67]), "=f"(d[68]), "=f"(d[69]), "=f"(d[70]), "=f"(d[71]), "=f"(d[72]), "=f"(d[73]), "=f"(d[74]), "=f"(d[75]), "=f"(d[76]), "=f"(d[77]), "=f"(d[78]), "=f"(d[79]), "=f"(d[80]), "=f"(d[81]), "=f"(d[82]), "=f"(d[83]), "=f"(d[84]), "=f"(d[85]), "=f"(d[86]), "=f"(d[87]), "=f"(d[88]), "=f"(d[89]), "=f"(d[90]), "=f"(d[91]), "=f"(d[92]), "=f"(d[93]), "=f"(d[94]), "=f"(d[95]), "=f"(d[96]), "=f"(d[97]), "=f"(d[98]), "=f"(d[99]), "=f"(d[100]), "=f"(d[101]), "=f"(d[102]), "=f"(d[103]), "=f"(d[104]), "=f"(d[105]), "=f"(d[106]), "=f"(d[107]), "=f"(d[108]), "=f"(d[109]), "=f"(d[110]), "=f"(d[111]), "=f"(d[112]), "=f"(d[113]), "=f"(d[114]), "=f"(d[115]), "=f"(d[116]), "=f"(d[117]), "=f"(d[118]), "=f"(d[119]), "=f"(d[120]), "=f"(d[121]), "=f"(d[122]), "=f"(d[123]), "=f"(d[124]), "=f"(d[125]), "=f"(d[126]), "=f"(d[127])
    : "l"(da), "l"(db));
}

template <int OFF, int IMM>
__device__ __forceinline__ void wgmma_sp_n128_init(float (&d)[128], const uint32_t* a, uint32_t base, uint32_t meta) {
  asm volatile(
    "{\n.reg .b32 lo;\n.reg .b64 db;\nadd.u32 lo, %68, %70;\nmov.b64 db, {lo, 0x40000040};\n"
    "wgmma.mma_async.sp.sync.aligned.m64n128k32.f32.bf16.bf16 {%0, %1, %2, %3, %4, %5, %6, %7, %8, %9, %10, %11, %12, %13, %14, %15, %16, %17, %18, %19, %20, %21, %22, %23, %24, %25, %26, %27, %28, %29, %30, %31, %32, %33, %34, %35, %36, %37, %38, %39, %40, %41, %42, %43, %44, %45, %46, %47, %48, %49, %50, %51, %52, %53, %54, %55, %56, %57, %58, %59, %60, %61, %62, %63}, {%64, %65, %66, %67}, db, %69, 0, 0, 1, 1, 1;\n}\n"
    : "=f"(d[OFF + 0]), "=f"(d[OFF + 1]), "=f"(d[OFF + 2]), "=f"(d[OFF + 3]), "=f"(d[OFF + 4]), "=f"(d[OFF + 5]), "=f"(d[OFF + 6]), "=f"(d[OFF + 7]), "=f"(d[OFF + 8]), "=f"(d[OFF + 9]), "=f"(d[OFF + 10]), "=f"(d[OFF + 11]), "=f"(d[OFF + 12]), "=f"(d[OFF + 13]), "=f"(d[OFF + 14]), "=f"(d[OFF + 15]), "=f"(d[OFF + 16]), "=f"(d[OFF + 17]), "=f"(d[OFF + 18]), "=f"(d[OFF + 19]), "=f"(d[OFF + 20]), "=f"(d[OFF + 21]), "=f"(d[OFF + 22]), "=f"(d[OFF + 23]), "=f"(d[OFF + 24]), "=f"(d[OFF + 25]), "=f"(d[OFF + 26]), "=f"(d[OFF + 27]), "=f"(d[OFF + 28]), "=f"(d[OFF + 29]), "=f"(d[OFF + 30]), "=f"(d[OFF + 31]), "=f"(d[OFF + 32]), "=f"(d[OFF + 33]), "=f"(d[OFF + 34]), "=f"(d[OFF + 35]), "=f"(d[OFF + 36]), "=f"(d[OFF + 37]), "=f"(d[OFF + 38]), "=f"(d[OFF + 39]), "=f"(d[OFF + 40]), "=f"(d[OFF + 41]), "=f"(d[OFF + 42]), "=f"(d[OFF + 43]), "=f"(d[OFF + 44]), "=f"(d[OFF + 45]), "=f"(d[OFF + 46]), "=f"(d[OFF + 47]), "=f"(d[OFF + 48]), "=f"(d[OFF + 49]), "=f"(d[OFF + 50]), "=f"(d[OFF + 51]), "=f"(d[OFF + 52]), "=f"(d[OFF + 53]), "=f"(d[OFF + 54]), "=f"(d[OFF + 55]), "=f"(d[OFF + 56]), "=f"(d[OFF + 57]), "=f"(d[OFF + 58]), "=f"(d[OFF + 59]), "=f"(d[OFF + 60]), "=f"(d[OFF + 61]), "=f"(d[OFF + 62]), "=f"(d[OFF + 63])
    : "r"(a[0]), "r"(a[1]), "r"(a[2]), "r"(a[3]), "r"(base), "r"(meta), "n"(IMM));
}

template <int TB, int OFF, int IMM>
__device__ __forceinline__ void wgmma_rs_n64_init(float (&d)[128], const uint32_t* a, uint32_t base) {
  asm volatile(
    "{\n.reg .b32 lo;\n.reg .b64 db;\nadd.u32 lo, %36, %38;\nmov.b64 db, {lo, 0x40000040};\n"
    "wgmma.mma_async.sync.aligned.m64n64k16.f32.bf16.bf16 {%0, %1, %2, %3, %4, %5, %6, %7, %8, %9, %10, %11, %12, %13, %14, %15, %16, %17, %18, %19, %20, %21, %22, %23, %24, %25, %26, %27, %28, %29, %30, %31}, {%32, %33, %34, %35}, db, 0, 1, 1, %37;\n}\n"
    : "=f"(d[OFF + 0]), "=f"(d[OFF + 1]), "=f"(d[OFF + 2]), "=f"(d[OFF + 3]), "=f"(d[OFF + 4]), "=f"(d[OFF + 5]), "=f"(d[OFF + 6]), "=f"(d[OFF + 7]), "=f"(d[OFF + 8]), "=f"(d[OFF + 9]), "=f"(d[OFF + 10]), "=f"(d[OFF + 11]), "=f"(d[OFF + 12]), "=f"(d[OFF + 13]), "=f"(d[OFF + 14]), "=f"(d[OFF + 15]), "=f"(d[OFF + 16]), "=f"(d[OFF + 17]), "=f"(d[OFF + 18]), "=f"(d[OFF + 19]), "=f"(d[OFF + 20]), "=f"(d[OFF + 21]), "=f"(d[OFF + 22]), "=f"(d[OFF + 23]), "=f"(d[OFF + 24]), "=f"(d[OFF + 25]), "=f"(d[OFF + 26]), "=f"(d[OFF + 27]), "=f"(d[OFF + 28]), "=f"(d[OFF + 29]), "=f"(d[OFF + 30]), "=f"(d[OFF + 31])
    : "r"(a[0]), "r"(a[1]), "r"(a[2]), "r"(a[3]), "r"(base), "n"(TB), "n"(IMM));
}

template <int OFF, int IMM>
__device__ __forceinline__ void wgmma_rs_n32(float (&d)[128], const uint32_t* a, uint32_t base) {
  asm volatile(
    "{\n.reg .b32 lo;\n.reg .b64 db;\nadd.u32 lo, %20, %21;\nmov.b64 db, {lo, 0x40000040};\n"
    "wgmma.mma_async.sync.aligned.m64n32k16.f32.bf16.bf16 {%0, %1, %2, %3, %4, %5, %6, %7, %8, %9, %10, %11, %12, %13, %14, %15}, {%16, %17, %18, %19}, db, 1, 1, 1, 1;\n}\n"
    : "+f"(d[OFF + 0]), "+f"(d[OFF + 1]), "+f"(d[OFF + 2]), "+f"(d[OFF + 3]), "+f"(d[OFF + 4]), "+f"(d[OFF + 5]), "+f"(d[OFF + 6]), "+f"(d[OFF + 7]), "+f"(d[OFF + 8]), "+f"(d[OFF + 9]), "+f"(d[OFF + 10]), "+f"(d[OFF + 11]), "+f"(d[OFF + 12]), "+f"(d[OFF + 13]), "+f"(d[OFF + 14]), "+f"(d[OFF + 15])
    : "r"(a[0]), "r"(a[1]), "r"(a[2]), "r"(a[3]), "r"(base), "n"(IMM));
}

template <int OFF, int IMM>
__device__ __forceinline__ void wgmma_rs_n32_init(float (&d)[128], const uint32_t* a, uint32_t base) {
  asm volatile(
    "{\n.reg .b32 lo;\n.reg .b64 db;\nadd.u32 lo, %20, %21;\nmov.b64 db, {lo, 0x40000040};\n"
    "wgmma.mma_async.sync.aligned.m64n32k16.f32.bf16.bf16 {%0, %1, %2, %3, %4, %5, %6, %7, %8, %9, %10, %11, %12, %13, %14, %15}, {%16, %17, %18, %19}, db, 0, 1, 1, 1;\n}\n"
    : "=f"(d[OFF + 0]), "=f"(d[OFF + 1]), "=f"(d[OFF + 2]), "=f"(d[OFF + 3]), "=f"(d[OFF + 4]), "=f"(d[OFF + 5]), "=f"(d[OFF + 6]), "=f"(d[OFF + 7]), "=f"(d[OFF + 8]), "=f"(d[OFF + 9]), "=f"(d[OFF + 10]), "=f"(d[OFF + 11]), "=f"(d[OFF + 12]), "=f"(d[OFF + 13]), "=f"(d[OFF + 14]), "=f"(d[OFF + 15])
    : "r"(a[0]), "r"(a[1]), "r"(a[2]), "r"(a[3]), "r"(base), "n"(IMM));
}

template <int OFF, bool INIT, int IMM>
__device__ __forceinline__ void g2_group(float (&d)[128], const uint32_t* a, uint32_t base) {
  if (INIT) wgmma_rs_n64_init<1, OFF, IMM>(d, a, base);
  else wgmma_rs_n64<1, OFF, IMM>(d, a, base);
  wgmma_rs_n64<1, OFF, IMM + 128>(d, a + 4, base);
  wgmma_rs_n64<1, OFF, IMM + 256>(d, a + 8, base);
  wgmma_rs_n64<1, OFF, IMM + 384>(d, a + 12, base);
  wgmma_rs_n64<1, OFF, IMM + 512>(d, a + 16, base);
  wgmma_rs_n64<1, OFF, IMM + 640>(d, a + 20, base);
  wgmma_rs_n64<1, OFF, IMM + 768>(d, a + 24, base);
  wgmma_rs_n64<1, OFF, IMM + 896>(d, a + 28, base);
}

template <int OFF, bool INIT, int IMM>
__device__ __forceinline__ void g2_group32(float (&d)[128], const uint32_t* a, uint32_t base) {
  if (INIT) wgmma_rs_n32_init<OFF, IMM>(d, a, base);
  else wgmma_rs_n32<OFF, IMM>(d, a, base);
  wgmma_rs_n32<OFF, IMM + 128>(d, a + 4, base);
  wgmma_rs_n32<OFF, IMM + 256>(d, a + 8, base);
  wgmma_rs_n32<OFF, IMM + 384>(d, a + 12, base);
  wgmma_rs_n32<OFF, IMM + 512>(d, a + 16, base);
  wgmma_rs_n32<OFF, IMM + 640>(d, a + 20, base);
  wgmma_rs_n32<OFF, IMM + 768>(d, a + 24, base);
  wgmma_rs_n32<OFF, IMM + 896>(d, a + 28, base);
}

template <int OFF, int IMM, int B, int E>
__device__ __forceinline__ void g2_part(float (&d)[128], const uint32_t* a, uint32_t base) {
  if constexpr (B < E) {
    wgmma_rs_n64<1, OFF, IMM + 128 * B>(d, a + 4 * B, base);
    g2_part<OFF, IMM, B + 1, E>(d, a, base);
  }
}
template <int I>
struct IC { static constexpr int value = I; };
template <int B, int E, class F>
__device__ __forceinline__ void static_for(F&& f) {
  if constexpr (B < E) {
    f(IC<B>{});
    static_for<B + 1, E>(f);
  }
}

__host__ __device__ constexpr int xslot(int k) { return (k & 1) ? 4 + (k >> 1) : (k >> 1); }
enum { K_V0, K_K1, K_V1, K_WI, K_W };
__host__ __device__ constexpr int n_kind(int n) {
  constexpr int t[16] = {K_V0, K_V0, K_WI, K_WI, K_V0, K_V0, K_WI, K_WI, K_K1, K_K1, K_V1, K_V1, K_K1, K_K1, K_V1, K_V1};
  return n < 16 ? t[n] : K_W;
}
__host__ __device__ constexpr int n_a(int n) {
  constexpr int t[16] = {0, 0, 0, 1, 1, 1, 2, 3, 0, 0, 0, 0, 1, 1, 1, 1};
  return n < 16 ? t[n] : n - 16;
}
__host__ __device__ constexpr int n_b(int n) {
  constexpr int t[16] = {0, 1, 0, 0, 0, 1, 0, 0, 0, 1, 0, 1, 0, 1, 0, 1};
  return n < 16 ? t[n] : 0;
}
__host__ __device__ constexpr int item_slot(int it) {
  constexpr int t[16] = {7, 8, 9, 10, 11, 12, 13, 3, 0, 1, 7, 8, 4, 5, 11, 12};
  constexpr int ws[12] = {9, 10, 0, 1, 13, 3, 7, 8, 4, 5, 11, 12};
  return it < 28 ? 7 + it % 7 : (it < 44 ? t[it - 28] : ws[(it - 44) % 12]);
}
__host__ __device__ constexpr int item_wait(int it) {
  constexpr int t[24] = {B_XEMPTY + 6, B_XEMPTY + 7, B_XEMPTY + 7, B_EMPTY + 28, B_EMPTY + 29, B_XEMPTY + 8, B_XEMPTY + 8,
                         B_EMPTY + 32, B_EMPTY + 33,
                         B_EMPTY + 30, B_EMPTY + 31, B_EMPTY + 36, B_EMPTY + 37, B_EMPTY + 34, B_EMPTY + 35, B_EMPTY + 38,
                         B_EMPTY + 39, B_EMPTY + 40, B_EMPTY + 41, B_EMPTY + 42, B_EMPTY + 43};
  return it < 35 ? B_EMPTY + it - 7 : (it < 56 ? t[it - 35] : B_EMPTY + it - 12);
}
__host__ __device__ constexpr int find_item(int kind, int a, int b) {
  for (int n = 0; n < 40; n++)
    if (n_kind(n) == kind && n_a(n) == a && n_b(n) == b) return 28 + n;
  return -1;
}
__host__ __device__ constexpr bool slot_reused(int it) { return it + 12 < NITEMS; }
__host__ __device__ constexpr int w_step(int g) { return g < 4 ? g >> 1 : 2 + ((g - 4) >> 2); }
__host__ __device__ constexpr int w_kq(int g) { return g < 4 ? 2 + (g & 1) : (g - 4) & 3; }

__device__ __forceinline__ int step_atom(int hg, int t) {
  if (t == 6) return min(hg, 6);
  int a = hg < 7 ? hg + 1 + t : 3 + t;
  const int m = hg < 7 ? 7 : 6;
  return a >= m ? a - m : a;
}
template <int OFF, int N>
__device__ __forceinline__ void pack_tile(float (&acc)[128], uint32_t (&p)[16]) {
  acc_fence<OFF, 2 * N>(acc);
#pragma unroll
  for (int i = 0; i < N; i++) p[i] = pack_bf16(acc[OFF + 2 * i], acc[OFF + 2 * i + 1]);
}
template <int OFF>
__device__ __forceinline__ void epi_stash(float (&acc)[128], uint32_t addr) {
  uint32_t p[16];
  pack_tile<OFF, 16>(acc, p);
#pragma unroll
  for (int q = 0; q < 4; q++)
    asm volatile("st.shared.v4.b32 [%0], {%1, %2, %3, %4};" ::"r"(addr + q * 512), "r"(p[4 * q]), "r"(p[4 * q + 1]),
                 "r"(p[4 * q + 2]), "r"(p[4 * q + 3])
                 : "memory");
}
__device__ __forceinline__ void tile_lds(uint32_t (&p)[16], uint32_t addr, uint32_t swp) {
#pragma unroll
  for (int q = 0; q < 4; q++)
    asm volatile("ld.shared.v4.b32 {%0, %1, %2, %3}, [%4];"
                 : "=r"(p[4 * q]), "=r"(p[4 * q + 1]), "=r"(p[4 * q + 2]), "=r"(p[4 * q + 3])
                 : "r"(addr + ((q * 512) ^ swp))
                 : "memory");
}
__device__ __forceinline__ void tile_ldg(uint32_t (&p)[16], const unsigned char* src, uint32_t swp, uint32_t l16) {
  ld_pkt2(src, l16 + swp, &p[0]);
  ld_pkt2(src, l16 + (swp ^ 1024u), &p[8]);
}
template <int OFF, bool ADD>
__device__ __forceinline__ void tile_acc(float (&acc)[128], uint32_t (&p)[16]) {
#pragma unroll
  for (int i = 0; i < 16; i++) {
    acc[OFF + 2 * i] = ADD ? acc[OFF + 2 * i] + bf_lo(p[i]) : bf_lo(p[i]);
    acc[OFF + 2 * i + 1] = ADD ? acc[OFF + 2 * i + 1] + bf_hi(p[i]) : bf_hi(p[i]);
  }
}
template <int OFF>
__device__ __forceinline__ void epi_store(float (&acc)[128], unsigned char* dst, uint32_t par, uint32_t l16) {
  uint32_t p[16];
  pack_tile<OFF, 16>(acc, p);
#pragma unroll
  for (int q = 0; q < 4; q++)
    st_pkt(dst + q * 512, l16, (p[4 * q] & ~1u) | par, p[4 * q + 1], p[4 * q + 2], p[4 * q + 3]);
}
__device__ __forceinline__ void park_sum(float (&acc)[128], uint32_t addr) {
#pragma unroll
  for (int q = 0; q < 4; q++)
    asm volatile("st.shared.v4.f32 [%0], {%1, %2, %3, %4};" ::"r"(addr + q * 512), "f"(acc[64 + 4 * q]),
                 "f"(acc[65 + 4 * q]), "f"(acc[66 + 4 * q]), "f"(acc[67 + 4 * q])
                 : "memory");
}
__device__ __forceinline__ void unpark_sum(float (&acc)[128], uint32_t addr) {
#pragma unroll
  for (int q = 0; q < 4; q++)
    asm volatile("ld.shared.v4.f32 {%0, %1, %2, %3}, [%4];"
                 : "=f"(acc[64 + 4 * q]), "=f"(acc[65 + 4 * q]), "=f"(acc[66 + 4 * q]), "=f"(acc[67 + 4 * q])
                 : "r"(addr + q * 512)
                 : "memory");
}
__device__ __forceinline__ void tile_validate(uint32_t (&p)[16], const unsigned char* src, uint32_t par, uint32_t swp,
                                              uint32_t l16, int tag) {
  int spins = 0;
  while (__any_sync(0xffffffffu, ((p[0] ^ par) | (p[4] ^ par) | (p[8] ^ par) | (p[12] ^ par)) & 1u) &&
         ++spins < (1 << 20)) {
    tile_ldg(p, src, swp, l16);
  }
}

__global__ void __launch_bounds__(384, 1) fused_attn_kernel(const __grid_constant__ Params prm) {
  extern __shared__ unsigned char smem_raw[];
  const uint32_t sbase = (smem_u32(smem_raw) + 1023) & ~1023u;
  const uint32_t bars = sbase + NSLOT * SLOT;

  const int tid = threadIdx.x;
  const int warp = __shfl_sync(0xffffffffu, tid >> 5, 0), lane = tid & 31;
  const int bid = blockIdx.x;
  const int rb = bid & 7, br = (bid >> 3) & 1, hg = bid >> 4;
  const int grp = br * 8 + rb;
  const int rsw = hg == 7;
  const int hsw = HSWAP ? (hg & 1) : 0;
  const int hd0 = 2 * hg + hsw, hd1 = 2 * hg + 1 - hsw;
  const CUtensorMap* maps = &prm.maps[br * 5];

  if (tid == 0) { TS(2, 3); }
  uint32_t pf0 = 0, pf1 = 0;
  if (warp >= 8) {
    asm volatile("setmaxnreg.dec.sync.aligned.u32 24;");
    if (warp != 8) {
      if (warp == 9 && lane == 0) {
#pragma unroll
        for (int i = 0; i < 10; i++) mbar_init(bars + 8 * (B_GATE + i), 4);
      }
      if (warp == 10 && lane == 0) {
        asm volatile("prefetch.tensormap [%0];" ::"l"((uint64_t)(maps + 2)) : "memory");
        asm volatile("prefetch.tensormap [%0];" ::"l"((uint64_t)(maps + 3)) : "memory");
        asm volatile("prefetch.tensormap [%0];" ::"l"((uint64_t)(maps + 4)) : "memory");
      }
      __syncwarp();
      asm volatile("bar.arrive 2, 384;" ::: "memory");
      asm volatile("bar.sync 0, 384;" ::: "memory");
    }
    if (warp == 8) {
      if (lane == 0) {
        TS(2, 0);
        mbar_init(bars + 8 * B_FULL, 1);
        mbar_init(bars + 8 * B_XFULL, 1);
        mbar_expect(bars + 8 * B_FULL, SLOT);
        tma_3d(sbase + 7 * SLOT, maps + 1, bars + 8 * B_FULL, 0, 0, 4 * hd1);
        mbar_expect(bars + 8 * B_XFULL, SLOT);
        tma_2d(sbase, maps + 0, bars + 8 * B_XFULL, 0, rb * 128);
        TS(2, 1);
#pragma unroll
        for (int i = 1; i < 7; i++) {
          mbar_init(bars + 8 * (B_XFULL + i), 1);
          mbar_init(bars + 8 * (B_FULL + i), 1);
        }
      }
      __syncwarp();
      asm volatile("bar.arrive 0, 384;" ::: "memory");
      if (lane == 0) {
#pragma unroll
        for (int i = 1; i < 7; i++) {
          mbar_expect(bars + 8 * (B_FULL + i), SLOT);
          tma_3d(sbase + (7 + i) * SLOT, maps + 1, bars + 8 * (B_FULL + i), 0, 32 * i, 4 * hd1);
          if (!(i & 1)) {
            const int k = i >> 1;
            mbar_expect(bars + 8 * (B_XFULL + k), SLOT);
            tma_2d(sbase + xslot(k) * SLOT, maps + 0, bars + 8 * (B_XFULL + k), 64 * k, rb * 128);
          }
        }
#pragma unroll
        for (int k = 4; k < 7; k++) {
          mbar_expect(bars + 8 * (B_XFULL + k), SLOT);
          tma_2d(sbase + xslot(k) * SLOT, maps + 0, bars + 8 * (B_XFULL + k), 64 * k, rb * 128);
        }
        TS(2, 2);
      }
      __syncwarp();
      asm volatile("bar.sync 2, 384;" ::: "memory");
      if (lane == 0) {
        const int kv0 = br ? hd0 : hg, kv1 = br ? hd1 : hg, b0 = rb * 4;
        static_for<7, NITEMS>([&](auto IT) {
          constexpr int it = decltype(IT)::value;
          const uint32_t fb = bars + 8 * (B_FULL + it);
          const uint32_t dst = sbase + item_slot(it) * SLOT;
          if constexpr (it >= 36 && it < 44) {
            if (!br) {
              mbar_arrive(fb);
              return;
            }
          }
          mbar_wait(bars + 8 * item_wait(it));
          mbar_expect(fb, SLOT);
          if constexpr (it < 28) {
            constexpr int hh = it >= 14, pc = it - 14 * hh;
            tma_3d(dst, maps + 1, fb, 0, 32 * pc, 4 * (hh ? hd0 : hd1));
          } else {
            constexpr int kind = n_kind(it - 28), a = n_a(it - 28), b = n_b(it - 28);
            if constexpr (kind == K_V0 || kind == K_V1) {
              tma_5d(dst, maps + 3, fb, 0, 0, b0 + 2 * (a ^ rsw), 16 * (kind == K_V1 ? kv1 : kv0), 2 * b);
            } else if constexpr (kind == K_K1) {
              tma_5d(dst, maps + 2, fb, 0, 0, b0 + 2 * (a ^ rsw), 2 * b, kv1);
            } else {
              constexpr int step = kind == K_WI ? a >> 1 : w_step(a), kq = kind == K_WI ? a & 1 : w_kq(a);
              tma_2d(dst, maps + 4, fb, 64 * step_atom(hg, step), 256 * (kq < 2 ? hd0 : hd1) + 128 * (kq & 1));
            }
          }
          if constexpr (it >= 22 && it <= 28 && !(it & 1)) {
            constexpr int j = (it - 22) >> 1;
            mbar_wait(bars + 8 * (B_XEMPTY + j));
            mbar_expect(bars + 8 * (B_KFULL + j), SLOT);
            tma_5d(sbase + xslot(j) * SLOT, maps + 2, bars + 8 * (B_KFULL + j), 0, 0, b0 + 2 * ((j & 1) ^ rsw), 2 * (j >> 1), kv0);
          }
        });
      }
      __syncwarp();
    } else {
      if (warp >= 12 - PFW) {
        const int H = br ? 16 : 8;
        const unsigned char* wq = prm.ptr[br * 5 + 3] + hg * 1024;
        const unsigned char* wo = prm.ptr[br * 5 + 4] + (size_t)(hg * 512) * 896;
        auto addr = [&](int b) -> const unsigned char* {
          if (b < 6) {
            int idx = b * 32 + lane;
            if (idx >= 168) idx = 167;
            if (idx < 112) return wq + (size_t)(224 + rb + 8 * (idx >> 2)) * 8192 + (idx & 3) * 256;
            idx -= 112;
            return wq + (size_t)(rb + 8 * (idx >> 1)) * 8192 + hsw * 512 + (idx & 1) * 256;
          }
          if (b < 22) {
            const int x = b - 6;
            return prm.ptr[br * 5 + 1 + (x >> 3)] + (size_t)((rb * 4 + ((x >> 1) & 3)) * H + (br ? hd0 : hg)) * 16384 +
                   (x & 1) * 8192 + lane * 256;
          }
          if (b < 24) return wo + (hsw * 256 + rb * 32 + lane) * 896 + step_atom(hg, b - 22) * 128;
          if (b < 32) {
            const int x = b - 24;
            return prm.ptr[6 + (x >> 2)] + (size_t)((rb * 4 + (x & 3)) * 16 + hd1) * 16384 + br * 8192 + lane * 256;
          }
          return wo + (min(b - 32, 6) * 8 + rb) * 8192 + lane * 256;
        };
        mbar_wait(bars + 8 * B_FULL);
        uint32_t sink = 0;
        constexpr int NB = WO_BY_STEP ? 44 : 40;
        int b = warp - (12 - PFW);
#pragma unroll 1
        for (; b < NB; b += PFD * PFW) {
          const unsigned char* p0 = addr(b);
          sink ^= pf0;
          pf0 = ld_pf(p0);
          const unsigned char* p1 = addr(min(b + PFW, NB - 1));
          sink ^= pf1;
          pf1 = ld_pf(p1);
        }
        asm volatile("st.shared.u32 [%0], %1;" ::"r"(bars + 8 * B_SINK), "r"(sink) : "memory");
      }
      if (warp >= 10 && lane == 0 && (hg < 6 || warp == 11)) {
        const int w = warp - 10;
        const unsigned char* src = g_part + (size_t)grp * GRP_BYTES + min(hg, 6) * (6 * BOX) + (w ^ rsw) * 8192;
#pragma unroll 1
        for (int u = 0; u < 5; u++) {
          mbar_wait(bars + 8 * (B_GATE + 2 * u + w));
          mbar_expect(bars + 8 * (B_INB + 2 * u + w), 8192);
          asm volatile("cp.async.bulk.shared::cluster.global.mbarrier::complete_tx::bytes [%0], [%1], 8192, [%2];" ::"r"(
                           sbase + (2 + 4 * w) * SLOT + (u & 1) * 8192),
                       "l"(src + u * BOX), "r"(bars + 8 * (B_INB + 2 * u + w))
                       : "memory");
        }
      }
    }
  } else {
    if (lane == 0) {
#pragma unroll
      for (int i = 0; i < 11; i++) mbar_init(bars + 8 * (14 + 11 * warp + i), 1);
#pragma unroll
      for (int i = 0; i < 9; i++) mbar_init(bars + 8 * (B_EMPTY + 9 * warp + i), 8);
    }
    __syncwarp();
    asm volatile("bar.arrive 2, 384;" ::: "memory");
    asm volatile("bar.sync 0, 384;" ::: "memory");
    asm volatile("setmaxnreg.inc.sync.aligned.u32 240;");
    const int w = warp >> 2;
    float acc[128];
    uint32_t qf0[64], qf1[64];
    uint32_t par;
    asm volatile("ld.relaxed.gpu.global.u32 %0, [%1];" : "=r"(par) : "l"(&g_epoch[bid * 8]) : "memory");
    const int rwarp = warp ^ (4 * rsw);
    unsigned char* gbase = g_part + (size_t)grp * GRP_BYTES + rwarp * TILE;
    const uint32_t l16 = lane * 16;

    int slot = 0, it = 0;
#pragma unroll
    for (int hh = 0; hh < 2; hh++) {
      {
        if (hh == 0) mbar_wait(bars + 8 * B_XFULL);
        mbar_wait(bars + 8 * (B_FULL + it));
        TSC(hh * 2);
        const uint64_t da = make_desc(sbase + (w ^ rsw) * 8192, 16, 1024);
        const uint64_t db = make_desc(sbase + (7 + slot) * SLOT, 4096, 1024);
        wg_fence();
        wgmma_ss_n256_init(acc, da, db);
        wgmma_ss_n256(acc, da + 2, db + 128);
        wg_commit();
        it++;
        if (++slot == 7) slot = 0;
      }
#pragma unroll 1
      for (int i = 1; i < 14; i++) {
        const int xs = xslot(i >> 1);
        if (hh == 0 && (i & 1) == 0) mbar_wait(bars + 8 * (B_XFULL + (i >> 1)));
        if (hh == 1 && i == 14 - SPRINT && w == 1) asm volatile("bar.sync 3, 256;" ::: "memory");
        mbar_wait(bars + 8 * (B_FULL + it));
        const uint64_t da = make_desc(sbase + xs * SLOT + (w ^ rsw) * 8192 + (i & 1) * 64, 16, 1024);
        const uint64_t db = make_desc(sbase + (7 + slot) * SLOT, 4096, 1024);
        wg_fence();
        wgmma_ss_n256(acc, da, db);
        wgmma_ss_n256(acc, da + 2, db + 128);
        wg_commit();
        if (hh == 1 && i == 13 && w == 0) asm volatile("bar.arrive 3, 256;" ::: "memory");
        wg_wait<1>();
        if (lane == 0) {
          mbar_arrive(bars + 8 * (B_EMPTY + it - 1));
          if (hh == 1 && (i & 1) == 0) mbar_arrive(bars + 8 * (B_XEMPTY + (i >> 1) - 1));
        }
        it++;
        if (++slot == 7) slot = 0;
      }
      wg_wait<0>();
      acc_fence<0, 128>(acc);
      TSC(hh * 2 + 1);
      if (lane == 0) {
        mbar_arrive(bars + 8 * (B_EMPTY + it - 1));
        if (hh == 1) mbar_arrive(bars + 8 * (B_XEMPTY + 6));
      }
#pragma unroll
      for (int i = 0; i < 64; i++) {
        if (hh == 0) qf1[i] = pack_bf16(acc[2 * i], acc[2 * i + 1]);
        else qf0[i] = pack_bf16(acc[2 * i], acc[2 * i + 1]);
      }
    }
    {
      const uint32_t t = qf0[62] & qf0[63] & blockIdx.y;
#pragma unroll
      for (int i = 0; i < 8; i++) qf0[i] ^= t;
    }
    const uint32_t epoch = __shfl_sync(0xffffffffu, par, 0) + 1;
    par = epoch & 1;

    const int jb = (warp >> 1) & 1;
    const uint32_t meta = jb ? 0xEEEEEEEEu : 0x44444444u;
    const uint32_t ustash = sbase + (2 + 4 * w) * SLOT + (warp & 3) * 2048;
#define stash (ustash + l16)
    uint32_t of0[64], of1[64];
    const uint32_t sb16 = (sbase & 0x3FFFF) >> 4;

    auto s_issue = [&](uint32_t(&q)[64], uint32_t bar_a, uint32_t bar_b, uint32_t slot_a, uint32_t slot_b) {
      mbar_wait(bar_a);
      {
        const uint32_t kb = sb16 + slot_a * 1024;
        wg_fence();
        wgmma_rs_n64_init<0, 0, 0x10000>(acc, &q[0], kb);
        static_for<1, 8>([&](auto S) {
          constexpr int s = decltype(S)::value;
          wgmma_rs_n64<0, 0, 0x10000 + (s >> 2) * 512 + (s & 3) * 2>(acc, &q[4 * s], kb);
        });
      }
      mbar_wait(bar_b);
      {
        const uint32_t kb = sb16 + slot_b * 1024;
        wg_fence();
        static_for<0, 8>([&](auto S) {
          constexpr int s = decltype(S)::value;
          wgmma_rs_n64<0, 0, 0x10000 + (s >> 2) * 512 + (s & 3) * 2>(acc, &q[32 + 4 * s], kb);
        });
      }
      wg_commit();
    };
    auto softmax_pv = [&](uint32_t(&o)[64], int ita, int itb, int slot_a, int slot_b, int tsb) {
      uint32_t pf[8];
      float v[16];
#pragma unroll
      for (int i = 0; i < 16; i++) v[i] = jb ? acc[16 + i] : acc[i];
      float m0 = fmaxf(fmaxf(fmaxf(v[0], v[1]), fmaxf(v[4], v[5])), fmaxf(fmaxf(v[8], v[9]), fmaxf(v[12], v[13])));
      float m1 = fmaxf(fmaxf(fmaxf(v[2], v[3]), fmaxf(v[6], v[7])), fmaxf(fmaxf(v[10], v[11]), fmaxf(v[14], v[15])));
      m0 = fmaxf(m0, __shfl_xor_sync(0xffffffffu, m0, 1));
      m1 = fmaxf(m1, __shfl_xor_sync(0xffffffffu, m1, 1));
      m0 = fmaxf(m0, __shfl_xor_sync(0xffffffffu, m0, 2));
      m1 = fmaxf(m1, __shfl_xor_sync(0xffffffffu, m1, 2));
      const float sc = 0.0625f * 1.4426950408889634f;
      const float n0 = -m0 * sc, n1 = -m1 * sc;
#pragma unroll
      for (int jj = 0; jj < 4; jj++) {
        v[4 * jj] = ex2(fmaf(v[4 * jj], sc, n0));
        v[4 * jj + 1] = ex2(fmaf(v[4 * jj + 1], sc, n0));
        v[4 * jj + 2] = ex2(fmaf(v[4 * jj + 2], sc, n1));
        v[4 * jj + 3] = ex2(fmaf(v[4 * jj + 3], sc, n1));
      }
      float s0 = ((v[0] + v[1]) + (v[4] + v[5])) + ((v[8] + v[9]) + (v[12] + v[13]));
      float s1 = ((v[2] + v[3]) + (v[6] + v[7])) + ((v[10] + v[11]) + (v[14] + v[15]));
      s0 += __shfl_xor_sync(0xffffffffu, s0, 1);
      s1 += __shfl_xor_sync(0xffffffffu, s1, 1);
      s0 += __shfl_xor_sync(0xffffffffu, s0, 2);
      s1 += __shfl_xor_sync(0xffffffffu, s1, 2);
      const float r0 = rcp(s0), r1 = rcp(s1);
#pragma unroll
      for (int jj = 0; jj < 4; jj++) {
        pf[2 * jj] = pack_bf16(v[4 * jj] * r0, v[4 * jj + 1] * r0);
        pf[2 * jj + 1] = pack_bf16(v[4 * jj + 2] * r1, v[4 * jj + 3] * r1);
      }
      TSC(tsb + 1);
      mbar_wait(bars + 8 * (B_FULL + ita));
      {
        const uint32_t vb = sb16 + slot_a * 1024;
        wg_fence();
        wgmma_sp_n128_init<0, 0x2000000>(acc, &pf[0], vb, meta);
        wgmma_sp_n128<0, 0x2000000 + 256>(acc, &pf[4], vb, meta);
        wg_commit();
      }
      mbar_wait(bars + 8 * (B_FULL + itb));
      {
        const uint32_t vb = sb16 + slot_b * 1024;
        wg_fence();
        wgmma_sp_n128_init<64, 0x2000000>(acc, &pf[0], vb, meta);
        wgmma_sp_n128<64, 0x2000000 + 256>(acc, &pf[4], vb, meta);
      }
      wg_commit();
      wg_wait<1>();
      acc_fence<0, 64>(acc);
#pragma unroll
      for (int i = 0; i < 32; i++) o[i] = pack_bf16(acc[2 * i], acc[2 * i + 1]);
#pragma unroll
      for (int i = 0; i < 32; i++) asm volatile("" : "+r"(o[i])::"memory");
      wg_wait<0>();
      acc_fence<64, 64>(acc);
      TSC(tsb + 2);
      if (lane == 0) {
        mbar_arrive2(bars + 8 * (B_EMPTY + ita));
        mbar_arrive2(bars + 8 * (B_EMPTY + itb));
      }
#pragma unroll
      for (int i = 32; i < 64; i++) o[i] = pack_bf16(acc[2 * i], acc[2 * i + 1]);
    };
#define SEL_IT(kind, b) (w ? find_item(kind, 1, b) : find_item(kind, 0, b))
#define SEL_SLOT(kind, b) (w ? item_slot(find_item(kind, 1, b)) : item_slot(find_item(kind, 0, b)))

    s_issue(qf0, bars + 8 * (B_KFULL + w), bars + 8 * (B_KFULL + 2 + w), 4 * w, 4 * w + 1);
    wg_wait<0>();
    acc_fence<0, 32>(acc);
    TSC(4);
    if (lane == 0) mbar_arrive2(bars + 8 * (B_XEMPTY + 7 + w));
    softmax_pv(qf0, SEL_IT(K_V0, 0), SEL_IT(K_V0, 1), SEL_SLOT(K_V0, 0), SEL_SLOT(K_V0, 1), 4);

    static_for<0, 4>([&](auto G) {
      constexpr int g = decltype(G)::value, c = g >> 1, kq = g & 1, it2 = find_item(K_WI, g, 0);
      mbar_wait(bars + 8 * (B_FULL + it2));
      wg_fence();
      g2_group<32 * (c & 1), kq == 0, 0x2000000 + item_slot(it2) * 1024>(acc, &qf0[32 * kq], sb16);
      wg_commit();
      if constexpr (g > 0) {
        wg_wait<1>();
        if (lane == 0) mbar_arrive(bars + 8 * (B_EMPTY + find_item(K_WI, g - 1, 0)));
      }
      if constexpr (g == 2) {
        mbar_wait(bars + 8 * (B_XEMPTY + 4 + w));
        epi_stash<0>(acc, stash);
      }
    });
    s_issue(qf1, bars + 8 * (B_FULL + SEL_IT(K_K1, 0)), bars + 8 * (B_FULL + SEL_IT(K_K1, 1)), SEL_SLOT(K_K1, 0),
            SEL_SLOT(K_K1, 1));
    wg_wait<1>();
    TSC(7);
    if (lane == 0) mbar_arrive(bars + 8 * (B_EMPTY + find_item(K_WI, 3, 0)));
    epi_stash<32>(acc, stash + 8192);
    wg_wait<0>();
    acc_fence<0, 32>(acc);
    TSC(12);
    if (lane == 0) {
      mbar_arrive2(bars + 8 * (B_EMPTY + SEL_IT(K_K1, 0)));
      mbar_arrive2(bars + 8 * (B_EMPTY + SEL_IT(K_K1, 1)));
    }
    {
      const uint32_t z = blockIdx.y;
#pragma unroll
      for (int i = 0; i < 64; i++) of0[i] = qf0[i] ^ z;
    }
    softmax_pv(of1, SEL_IT(K_V1, 0), SEL_IT(K_V1, 1), SEL_SLOT(K_V1, 0), SEL_SLOT(K_V1, 1), 12);

    const unsigned char* inbox = gbase + min(hg, 6) * (6 * BOX);
    const unsigned char* inbox_x = gbase + (42 + min(hg, 6)) * BOX;
    const bool owner = hg < 6 || w == 1;
    constexpr uint32_t swp = 0;
    uint32_t pk[16];
    auto ask = [&](int u) {
      if (lane == 0) mbar_arrive(bars + 8 * (B_GATE + 2 * u + w));
    };
    auto fold = [&](auto U) {
      constexpr int u = decltype(U)::value;
      if (owner) {
        mbar_wait(bars + 8 * (B_INB + 2 * u + w));
        tile_lds(pk, stash + (u & 1) * 8192, swp);
        tile_validate(pk, inbox + u * BOX, par, swp, l16, u);
        tile_acc<64, true>(acc, pk);
      }
    };
    tile_lds(pk, stash, 0);
    tile_acc<0, false>(acc, pk);
    static_for<0, 20>([&](auto G) {
      constexpr int g = decltype(G)::value, s = w_step(g), kq = w_kq(g), it2 = find_item(K_W, g, 0);
      mbar_wait(bars + 8 * (B_FULL + it2));
      if constexpr (kq == 0 && s >= PP0)
        if (s > PP0 || w == 1) asm volatile("bar.sync %0, 256;" ::"r"(4 + w) : "memory");
      wg_fence();
      if constexpr (kq == 3 && s >= PP0) {
        g2_part<32 * (s & 1), 0x2000000 + item_slot(it2) * 1024, 0, PP_AT>(acc, &of1[32], sb16);
        asm volatile("bar.arrive %0, 256;" ::"r"(5 - w) : "memory");
        g2_part<32 * (s & 1), 0x2000000 + item_slot(it2) * 1024, PP_AT, 8>(acc, &of1[32], sb16);
      } else {
        g2_group<32 * (s & 1), kq == 0, 0x2000000 + item_slot(it2) * 1024>(
            acc, kq < 2 ? &of0[32 * (kq & 1)] : &of1[32 * (kq & 1)], sb16);
      }
      wg_commit();
      if constexpr (g == 0) {
        tile_lds(pk, stash + 8192, 0);
        tile_acc<32, false>(acc, pk);
      }
      if constexpr (s == 2 && kq == 1) {
        ask(0);
#pragma unroll
        for (int i = 0; i < 32; i++) acc[64 + i] = 0.f;
      }
      if constexpr (s >= 3 && kq == 0) ask(s - 2);
      if constexpr (s == 5 && kq == ASK4) ask(4);
      if constexpr (s == 5 && kq == 0)
        if (tid == 0) g_epoch[bid * 8] = epoch;
      if constexpr (kq == 3) {
        wg_wait<0>();
        if (lane == 0) {
          if constexpr (slot_reused(it2 - 1)) mbar_arrive(bars + 8 * (B_EMPTY + it2 - 1));
          if constexpr (slot_reused(it2)) mbar_arrive(bars + 8 * (B_EMPTY + it2));
        }
        TSC(15 + s);
        const int a = step_atom(hg, s);
        epi_store<32 * (s & 1)>(acc, gbase + (hg < 7 ? a * 6 + s : 42 + a) * BOX, par, l16);
        if constexpr (s >= 2) fold(IC<s - 2>{});
      } else if constexpr (g > 0 && w_step(g - 1) == s) {
        wg_wait<1>();
        if constexpr (slot_reused(it2 - 1))
          if (lane == 0) mbar_arrive(bars + 8 * (B_EMPTY + it2 - 1));
      }
    });
    {
      uint32_t pl[16];
      asm volatile("bar.sync %0, 256;" ::"r"(4 + w) : "memory");
      static_for<0, 4>([&](auto KQ) {
        constexpr int kq = decltype(KQ)::value, it2 = find_item(K_W, 20 + kq, 0);
        mbar_wait(bars + 8 * (B_FULL + it2));
        wg_fence();
        if constexpr (kq == 3) {
          g2_part<64, 0x2000000 + item_slot(it2) * 1024, 0, PP_AT>(acc, &of1[32], sb16);
          if (w == 0) asm volatile("bar.arrive 5, 256;" ::: "memory");
          g2_part<64, 0x2000000 + item_slot(it2) * 1024, PP_AT, 8>(acc, &of1[32], sb16);
        } else {
          g2_part<64, 0x2000000 + item_slot(it2) * 1024, 0, 8>(acc, kq < 2 ? &of0[32 * (kq & 1)] : &of1[0], sb16);
        }
        if constexpr (kq == TAIL_LD)
          if (owner) tile_ldg(pk, inbox + 5 * BOX, swp, l16);
        if constexpr (kq == TAIL_LDX)
          if (owner) tile_ldg(pl, inbox_x, swp, l16);
      });
      wg_commit();
      TSC(21);
      wg_wait<0>();
      if (owner) {
        acc_fence<64, 32>(acc);
        tile_validate(pk, inbox + 5 * BOX, par, swp, l16, 5);
        tile_acc<64, true>(acc, pk);
        fold(IC<4>{});
        tile_validate(pl, inbox_x, par, swp, l16, 6);
        tile_acc<64, true>(acc, pl);
        TSC(22);
        const int t = lane & 3;
        __nv_bfloat16* o =
            prm.out + (size_t)(rb * 128 + rwarp * 16 + (lane >> 2)) * 896 + br * 448 + 64 * min(hg, 6) + 8 * t;
#pragma unroll
        for (int m = 0; m < 2; m++) {
#pragma unroll
          for (int h = 0; h < 2; h++) {
            uint32_t x[4];
#pragma unroll
            for (int j = 0; j < 4; j++)
              x[j] = pack_bf16(acc[64 + 16 * m + 4 * j + 2 * h], acc[65 + 16 * m + 4 * j + 2 * h]);
            {
              const bool od = t & 1;
              const uint32_t r0 = __shfl_xor_sync(0xffffffffu, od ? x[0] : x[1], 1);
              const uint32_t r1 = __shfl_xor_sync(0xffffffffu, od ? x[2] : x[3], 1);
              if (od) { x[0] = r0; x[2] = r1; } else { x[1] = r0; x[3] = r1; }
            }
            {
              const bool hi = t & 2;
              const uint32_t r0 = __shfl_xor_sync(0xffffffffu, hi ? x[0] : x[2], 2);
              const uint32_t r1 = __shfl_xor_sync(0xffffffffu, hi ? x[1] : x[3], 2);
              if (hi) { x[0] = r0; x[1] = r1; } else { x[2] = r0; x[3] = r1; }
            }
            *reinterpret_cast<uint4*>(o + h * 8 * 896 + 32 * m) = make_uint4(x[0], x[1], x[2], x[3]);
          }
        }
      } else {
        epi_store<64>(acc, gbase + 48 * BOX, par, l16);
        TSC(22);
      }
    }
    TSC(23);
  }
}

typedef CUresult (*EncodeFn)(CUtensorMap*, CUtensorMapDataType, cuuint32_t, void*, const cuuint64_t*, const cuuint64_t*,
                             const cuuint32_t*, const cuuint32_t*, CUtensorMapInterleave, CUtensorMapSwizzle,
                             CUtensorMapL2promotion, CUtensorMapFloatOOBfill);

void encode(EncodeFn fn, CUtensorMap* m, int rank, const void* ptr, const cuuint64_t* dims, const cuuint64_t* strides,
            const cuuint32_t* box) {
  cuuint32_t es[5] = {1, 1, 1, 1, 1};
  fn(m, CU_TENSOR_MAP_DATA_TYPE_BFLOAT16, rank, const_cast<void*>(ptr), dims, strides, box, es,
     CU_TENSOR_MAP_INTERLEAVE_NONE, CU_TENSOR_MAP_SWIZZLE_128B, CU_TENSOR_MAP_L2_PROMOTION_L2_256B,
     CU_TENSOR_MAP_FLOAT_OOB_FILL_NONE);
}

}

extern "C" void kernel_launch(void* const* d_in, const int* in_sizes, int n_in, void* d_out, int out_size) {
  (void)in_sizes; (void)n_in; (void)out_size;
  void* fnp = nullptr;
  cudaDriverEntryPointQueryResult qr;
  cudaGetDriverEntryPoint("cuTensorMapEncodeTiled", &fnp, cudaEnableDefault, &qr);
  EncodeFn fn = (EncodeFn)fnp;
  Params prm;
  for (int br = 0; br < 2; br++) {
    const void* x = d_in[br * 5 + 0];
    const void* kc = d_in[br * 5 + 1];
    const void* vc = d_in[br * 5 + 2];
    const void* wq = d_in[br * 5 + 3];
    const void* wo = d_in[br * 5 + 4];
    const cuuint64_t H = br ? 16 : 8;
    {
      cuuint64_t dims[2] = {448, 1024}, str[1] = {896};
      cuuint32_t box[2] = {64, 128};
      encode(fn, &prm.maps[br * 5 + 0], 2, x, dims, str, box);
    }
    {
      cuuint64_t dims[3] = {64, 448, 64}, str[2] = {8192, 128};
      cuuint32_t box[3] = {64, 32, 4};
      encode(fn, &prm.maps[br * 5 + 1], 3, wq, dims, str, box);
    }
    {
      cuuint64_t dims[5] = {64, 32, 32, 4, H}, str[4] = {512, H * 16384, 128, 16384};
      cuuint32_t box[5] = {64, 32, 2, 2, 1};
      encode(fn, &prm.maps[br * 5 + 2], 5, kc, dims, str, box);
    }
    {
      cuuint64_t dims[5] = {64, 2, 32, 16 * H, 4}, str[4] = {512, H * 16384, 1024, 128};
      cuuint32_t box[5] = {64, 2, 2, 16, 2};
      encode(fn, &prm.maps[br * 5 + 3], 5, vc, dims, str, box);
    }
    {
      cuuint64_t dims[2] = {448, 4096}, str[1] = {896};
      cuuint32_t box[2] = {64, 128};
      encode(fn, &prm.maps[br * 5 + 4], 2, wo, dims, str, box);
    }
  }
  for (int i = 0; i < 10; i++) prm.ptr[i] = (const unsigned char*)d_in[i];
  prm.out = (__nv_bfloat16*)d_out;
  cudaFuncSetAttribute(fused_attn_kernel, cudaFuncAttributeMaxDynamicSharedMemorySize, SMEM_BYTES);
  fused_attn_kernel<<<128, 384, SMEM_BYTES>>>(prm);
}
```

```cpp
#include <cuda_runtime.h>
#include <cuda_bf16.h>
#include <cuda.h>
#include <stdint.h>

namespace {

constexpr int SLOT = 16384;
constexpr int NSLOT = 14;
constexpr int NITEMS = 68;
constexpr int B_XFULL = 0;
constexpr int B_FULL = 7;
constexpr int B_KFULL = 79;
constexpr int B_INB = 83;
constexpr int B_EMPTY = 102;
constexpr int B_XEMPTY = 165;
constexpr int B_GATE = 174;
constexpr int B_SINK = 184;
constexpr int NBAR = 185;
constexpr int SMEM_BYTES = 1024 + NSLOT * SLOT + NBAR * 8;
constexpr int TILE = 2048;
constexpr int BOX = 8 * TILE;
constexpr int GRP_BYTES = 49 * BOX;

struct Params {
  CUtensorMap maps[10];
  const unsigned char* ptr[10];
  __nv_bfloat16* out;
};

__device__ __align__(1024) unsigned char g_part[16 * GRP_BYTES];
__device__ unsigned int g_epoch[128 * 8];


__device__ __forceinline__ uint32_t smem_u32(const void* p) { return (uint32_t)__cvta_generic_to_shared(p); }
__device__ __forceinline__ void mbar_init(uint32_t a, uint32_t c) {
  asm volatile("mbarrier.init.shared::cta.b64 [%0], %1;" ::"r"(a), "r"(c) : "memory");
}
__device__ __forceinline__ void mbar_expect(uint32_t a, uint32_t b) {
  asm volatile("mbarrier.arrive.expect_tx.shared::cta.b64 _, [%0], %1;" ::"r"(a), "r"(b) : "memory");
}
__device__ __forceinline__ void mbar_arrive(uint32_t a) {
  asm volatile("mbarrier.arrive.shared::cta.b64 _, [%0];" ::"r"(a) : "memory");
}
__device__ __forceinline__ void mbar_arrive2(uint32_t a) {
  asm volatile("mbarrier.arrive.shared::cta.b64 _, [%0], 2;" ::"r"(a) : "memory");
}
__device__ __forceinline__ void mbar_wait(uint32_t a) {
  asm volatile(
      "{\n.reg .pred P;\n.reg .u32 n;\nmov.u32 n, 0;\n"
      "LW:\nmbarrier.try_wait.parity.shared::cta.b64 P, [%0], 0;\n"
      "@P bra LD;\nadd.u32 n, n, 1;\nsetp.lt.u32 P, n, 0x100000;\n@P bra LW;\n"
      "LD:\n}" ::"r"(a)
      : "memory");
}
__device__ __forceinline__ void tma_2d(uint32_t dst, const CUtensorMap* m, uint32_t bar, int c0, int c1) {
  asm volatile(
      "cp.async.bulk.tensor.2d.shared::cluster.global.mbarrier::complete_tx::bytes [%0], [%1, {%3, %4}], [%2];" ::"r"(dst),
      "l"((uint64_t)m), "r"(bar), "r"(c0), "r"(c1)
      : "memory");
}
__device__ __forceinline__ void tma_3d(uint32_t dst, const CUtensorMap* m, uint32_t bar, int c0, int c1, int c2) {
  asm volatile(
      "cp.async.bulk.tensor.3d.shared::cluster.global.mbarrier::complete_tx::bytes [%0], [%1, {%3, %4, %5}], [%2];" ::"r"(
          dst),
      "l"((uint64_t)m), "r"(bar), "r"(c0), "r"(c1), "r"(c2)
      : "memory");
}
__device__ __forceinline__ void tma_5d(uint32_t dst, const CUtensorMap* m, uint32_t bar, int c0, int c1, int c2, int c3,
                                       int c4) {
  asm volatile(
      "cp.async.bulk.tensor.5d.shared::cluster.global.mbarrier::complete_tx::bytes [%0], [%1, {%3, %4, %5, %6, %7}], "
      "[%2];" ::"r"(dst),
      "l"((uint64_t)m), "r"(bar), "r"(c0), "r"(c1), "r"(c2), "r"(c3), "r"(c4)
      : "memory");
}
__device__ __forceinline__ uint32_t ld_pf(const void* p) {
  uint32_t v;
  asm volatile("ld.global.cg.L2::256B.u32 %0, [%1];" : "=r"(v) : "l"(p));
  return v;
}
__device__ __forceinline__ void wg_fence() { asm volatile("wgmma.fence.sync.aligned;" ::: "memory"); }
__device__ __forceinline__ void wg_commit() { asm volatile("wgmma.commit_group.sync.aligned;" ::: "memory"); }
template <int N>
__device__ __forceinline__ void wg_wait() {
  asm volatile("wgmma.wait_group.sync.aligned %0;" ::"n"(N) : "memory");
}
template <int OFF, int N>
__device__ __forceinline__ void acc_fence(float (&d)[128]) {
#pragma unroll
  for (int i = 0; i < N; i++) asm volatile("" : "+f"(d[OFF + i])::"memory");
}
__device__ __forceinline__ uint32_t pack_bf16(float lo, float hi) {
  uint32_t r;
  asm("cvt.rn.bf16x2.f32 %0, %1, %2;" : "=r"(r) : "f"(hi), "f"(lo));
  return r;
}
__device__ __forceinline__ float bf_lo(uint32_t v) { return __uint_as_float(v << 16); }
__device__ __forceinline__ float bf_hi(uint32_t v) { return __uint_as_float(v & 0xffff0000u); }
__device__ __forceinline__ float ex2(float x) {
  float r;
  asm("ex2.approx.ftz.f32 %0, %1;" : "=f"(r) : "f"(x));
  return r;
}
__device__ __forceinline__ float rcp(float x) {
  float r;
  asm("rcp.approx.ftz.f32 %0, %1;" : "=f"(r) : "f"(x));
  return r;
}
__device__ __forceinline__ void st_pkt(const void* p, uint32_t off, uint32_t a, uint32_t b, uint32_t c, uint32_t d) {
  asm volatile(
      "{\n.reg .b64 lo, hi, ad;\n.reg .b128 v;\nmov.b64 lo, {%2, %3};\nmov.b64 hi, {%4, %5};\nmov.b128 v, {lo, hi};\n"
      "cvt.u64.u32 ad, %1;\nadd.u64 ad, ad, %0;\nst.relaxed.gpu.global.b128 [ad], v;\n}" ::"l"(p),
      "r"(off), "r"(a), "r"(b), "r"(c), "r"(d)
      : "memory");
}
__device__ __forceinline__ void ld_pkt2(const void* p, uint32_t off, uint32_t* v) {
  asm volatile(
      "{\n.reg .b64 lo, hi, ad;\n.reg .b128 v, w;\ncvt.u64.u32 ad, %9;\nadd.u64 ad, ad, %8;\n"
      "ld.relaxed.gpu.global.b128 v, [ad];\nld.relaxed.gpu.global.b128 w, [ad+512];\n"
      "mov.b128 {lo, hi}, v;\nmov.b64 {%0, %1}, lo;\nmov.b64 {%2, %3}, hi;\n"
      "mov.b128 {lo, hi}, w;\nmov.b64 {%4, %5}, lo;\nmov.b64 {%6, %7}, hi;\n}"
      : "=r"(v[0]), "=r"(v[1]), "=r"(v[2]), "=r"(v[3]), "=r"(v[4]), "=r"(v[5]), "=r"(v[6]), "=r"(v[7])
      : "l"(p), "r"(off)
      : "memory");
}
__device__ __forceinline__ uint64_t make_desc(uint32_t addr, uint32_t lbo, uint32_t sbo) {
  return (uint64_t)((addr & 0x3FFFF) >> 4) | ((uint64_t)(lbo >> 4) << 16) | ((uint64_t)(sbo >> 4) << 32) |
         ((uint64_t)1 << 62);
}

__device__ __forceinline__ void wgmma_ss_n256(float (&d)[128], uint64_t da, uint64_t db) {
  asm volatile(
    "wgmma.mma_async.sync.aligned.m64n256k16.f32.bf16.bf16 {%0, %1, %2, %3, %4, %5, %6, %7, %8, %9, %10, %11, %12, %13, %14, %15, %16, %17, %18, %19, %20, %21, %22, %23, %24, %25, %26, %27, %28, %29, %30, %31, %32, %33, %34, %35, %36, %37, %38, %39, %40, %41, %42, %43, %44, %45, %46, %47, %48, %49, %50, %51, %52, %53, %54, %55, %56, %57, %58, %59, %60, %61, %62, %63, %64, %65, %66, %67, %68, %69, %70, %71, %72, %73, %74, %75, %76, %77, %78, %79, %80, %81, %82, %83, %84, %85, %86, %87, %88, %89, %90, %91, %92, %93, %94, %95, %96, %97, %98, %99, %100, %101, %102, %103, %104, %105, %106, %107, %108, %109, %110, %111, %112, %113, %114, %115, %116, %117, %118, %119, %120, %121, %122, %123, %124, %125, %126, %127}, %128, %129, 1, 1, 1, 0, 1;\n"
    : "+f"(d[0]), "+f"(d[1]), "+f"(d[2]), "+f"(d[3]), "+f"(d[4]), "+f"(d[5]), "+f"(d[6]), "+f"(d[7]), "+f"(d[8]), "+f"(d[9]), "+f"(d[10]), "+f"(d[11]), "+f"(d[12]), "+f"(d[13]), "+f"(d[14]), "+f"(d[15]), "+f"(d[16]), "+f"(d[17]), "+f"(d[18]), "+f"(d[19]), "+f"(d[20]), "+f"(d[21]), "+f"(d[22]), "+f"(d[23]), "+f"(d[24]), "+f"(d[25]), "+f"(d[26]), "+f"(d[27]), "+f"(d[28]), "+f"(d[29]), "+f"(d[30]), "+f"(d[31]), "+f"(d[32]), "+f"(d[33]), "+f"(d[34]), "+f"(d[35]), "+f"(d[36]), "+f"(d[37]), "+f"(d[38]), "+f"(d[39]), "+f"(d[40]), "+f"(d[41]), "+f"(d[42]), "+f"(d[43]), "+f"(d[44]), "+f"(d[45]), "+f"(d[46]), "+f"(d[47]), "+f"(d[48]), "+f"(d[49]), "+f"(d[50]), "+f"(d[51]), "+f"(d[52]), "+f"(d[53]), "+f"(d[54]), "+f"(d[55]), "+f"(d[56]), "+f"(d[57]), "+f"(d[58]), "+f"(d[59]), "+f"(d[60]), "+f"(d[61]), "+f"(d[62]), "+f"(d[63]), "+f"(d[64]), "+f"(d[65]), "+f"(d[66]), "+f"(d[67]), "+f"(d[68]), "+f"(d[69]), "+f"(d[70]), "+f"(d[71]), "+f"(d[72]), "+f"(d[73]), "+f"(d[74]), "+f"(d[75]), "+f"(d[76]), "+f"(d[77]), "+f"(d[78]), "+f"(d[79]), "+f"(d[80]), "+f"(d[81]), "+f"(d[82]), "+f"(d[83]), "+f"(d[84]), "+f"(d[85]), "+f"(d[86]), "+f"(d[87]), "+f"(d[88]), "+f"(d[89]), "+f"(d[90]), "+f"(d[91]), "+f"(d[92]), "+f"(d[93]), "+f"(d[94]), "+f"(d[95]), "+f"(d[96]), "+f"(d[97]), "+f"(d[98]), "+f"(d[99]), "+f"(d[100]), "+f"(d[101]), "+f"(d[102]), "+f"(d[103]), "+f"(d[104]), "+f"(d[105]), "+f"(d[106]), "+f"(d[107]), "+f"(d[108]), "+f"(d[109]), "+f"(d[110]), "+f"(d[111]), "+f"(d[112]), "+f"(d[113]), "+f"(d[114]), "+f"(d[115]), "+f"(d[116]), "+f"(d[117]), "+f"(d[118]), "+f"(d[119]), "+f"(d[120]), "+f"(d[121]), "+f"(d[122]), "+f"(d[123]), "+f"(d[124]), "+f"(d[125]), "+f"(d[126]), "+f"(d[127])
    : "l"(da), "l"(db));
}

template <int OFF, int IMM>
__device__ __forceinline__ void wgmma_sp_n128(float (&d)[128], const uint32_t* a, uint32_t base, uint32_t meta) {
  asm volatile(
    "{\n.reg .b32 lo;\n.reg .b64 db;\nadd.u32 lo, %68, %70;\nmov.b64 db, {lo, 0x40000040};\n"
    "wgmma.mma_async.sp.sync.aligned.m64n128k32.f32.bf16.bf16 {%0, %1, %2, %3, %4, %5, %6, %7, %8, %9, %10, %11, %12, %13, %14, %15, %16, %17, %18, %19, %20, %21, %22, %23, %24, %25, %26, %27, %28, %29, %30, %31, %32, %33, %34, %35, %36, %37, %38, %39, %40, %41, %42, %43, %44, %45, %46, %47, %48, %49, %50, %51, %52, %53, %54, %55, %56, %57, %58, %59, %60, %61, %62, %63}, {%64, %65, %66, %67}, db, %69, 0, 1, 1, 1, 1;\n}\n"
    : "+f"(d[OFF + 0]), "+f"(d[OFF + 1]), "+f"(d[OFF + 2]), "+f"(d[OFF + 3]), "+f"(d[OFF + 4]), "+f"(d[OFF + 5]), "+f"(d[OFF + 6]), "+f"(d[OFF + 7]), "+f"(d[OFF + 8]), "+f"(d[OFF + 9]), "+f"(d[OFF + 10]), "+f"(d[OFF + 11]), "+f"(d[OFF + 12]), "+f"(d[OFF + 13]), "+f"(d[OFF + 14]), "+f"(d[OFF + 15]), "+f"(d[OFF + 16]), "+f"(d[OFF + 17]), "+f"(d[OFF + 18]), "+f"(d[OFF + 19]), "+f"(d[OFF + 20]), "+f"(d[OFF + 21]), "+f"(d[OFF + 22]), "+f"(d[OFF + 23]), "+f"(d[OFF + 24]), "+f"(d[OFF + 25]), "+f"(d[OFF + 26]), "+f"(d[OFF + 27]), "+f"(d[OFF + 28]), "+f"(d[OFF + 29]), "+f"(d[OFF + 30]), "+f"(d[OFF + 31]), "+f"(d[OFF + 32]), "+f"(d[OFF + 33]), "+f"(d[OFF + 34]), "+f"(d[OFF + 35]), "+f"(d[OFF + 36]), "+f"(d[OFF + 37]), "+f"(d[OFF + 38]), "+f"(d[OFF + 39]), "+f"(d[OFF + 40]), "+f"(d[OFF + 41]), "+f"(d[OFF + 42]), "+f"(d[OFF + 43]), "+f"(d[OFF + 44]), "+f"(d[OFF + 45]), "+f"(d[OFF + 46]), "+f"(d[OFF + 47]), "+f"(d[OFF + 48]), "+f"(d[OFF + 49]), "+f"(d[OFF + 50]), "+f"(d[OFF + 51]), "+f"(d[OFF + 52]), "+f"(d[OFF + 53]), "+f"(d[OFF + 54]), "+f"(d[OFF + 55]), "+f"(d[OFF + 56]), "+f"(d[OFF + 57]), "+f"(d[OFF + 58]), "+f"(d[OFF + 59]), "+f"(d[OFF + 60]), "+f"(d[OFF + 61]), "+f"(d[OFF + 62]), "+f"(d[OFF + 63])
    : "r"(a[0]), "r"(a[1]), "r"(a[2]), "r"(a[3]), "r"(base), "r"(meta), "n"(IMM));
}

template <int TB, int OFF, int IMM>
__device__ __forceinline__ void wgmma_rs_n64(float (&d)[128], const uint32_t* a, uint32_t base) {
  asm volatile(
    "{\n.reg .b32 lo;\n.reg .b64 db;\nadd.u32 lo, %36, %38;\nmov.b64 db, {lo, 0x40000040};\n"
    "wgmma.mma_async.sync.aligned.m64n64k16.f32.bf16.bf16 {%0, %1, %2, %3, %4, %5, %6, %7, %8, %9, %10, %11, %12, %13, %14, %15, %16, %17, %18, %19, %20, %21, %22, %23, %24, %25, %26, %27, %28, %29, %30, %31}, {%32, %33, %34, %35}, db, 1, 1, 1, %37;\n}\n"
    : "+f"(d[OFF + 0]), "+f"(d[OFF + 1]), "+f"(d[OFF + 2]), "+f"(d[OFF + 3]), "+f"(d[OFF + 4]), "+f"(d[OFF + 5]), "+f"(d[OFF + 6]), "+f"(d[OFF + 7]), "+f"(d[OFF + 8]), "+f"(d[OFF + 9]), "+f"(d[OFF + 10]), "+f"(d[OFF + 11]), "+f"(d[OFF + 12]), "+f"(d[OFF + 13]), "+f"(d[OFF + 14]), "+f"(d[OFF + 15]), "+f"(d[OFF + 16]), "+f"(d[OFF + 17]), "+f"(d[OFF + 18]), "+f"(d[OFF + 19]), "+f"(d[OFF + 20]), "+f"(d[OFF + 21]), "+f"(d[OFF + 22]), "+f"(d[OFF + 23]), "+f"(d[OFF + 24]), "+f"(d[OFF + 25]), "+f"(d[OFF + 26]), "+f"(d[OFF + 27]), "+f"(d[OFF + 28]), "+f"(d[OFF + 29]), "+f"(d[OFF + 30]), "+f"(d[OFF + 31])
    : "r"(a[0]), "r"(a[1]), "r"(a[2]), "r"(a[3]), "r"(base), "n"(TB), "n"(IMM));
}

__device__ __forceinline__ void wgmma_ss_n256_init(float (&d)[128], uint64_t da, uint64_t db) {
  asm volatile(
    "wgmma.mma_async.sync.aligned.m64n256k16.f32.bf16.bf16 {%0, %1, %2, %3, %4, %5, %6, %7, %8, %9, %10, %11, %12, %13, %14, %15, %16, %17, %18, %19, %20, %21, %22, %23, %24, %25, %26, %27, %28, %29, %30, %31, %32, %33, %34, %35, %36, %37, %38, %39, %40, %41, %42, %43, %44, %45, %46, %47, %48, %49, %50, %51, %52, %53, %54, %55, %56, %57, %58, %59, %60, %61, %62, %63, %64, %65, %66, %67, %68, %69, %70, %71, %72, %73, %74, %75, %76, %77, %78, %79, %80, %81, %82, %83, %84, %85, %86, %87, %88, %89, %90, %91, %92, %93, %94, %95, %96, %97, %98, %99, %100, %101, %102, %103, %104, %105, %106, %107, %108, %109, %110, %111, %112, %113, %114, %115, %116, %117, %118, %119, %120, %121, %122, %123, %124, %125, %126, %127}, %128, %129, 0, 1, 1, 0, 1;\n"
    : "=f"(d[0]), "=f"(d[1]), "=f"(d[2]), "=f"(d[3]), "=f"(d[4]), "=f"(d[5]), "=f"(d[6]), "=f"(d[7]), "=f"(d[8]), "=f"(d[9]), "=f"(d[10]), "=f"(d[11]), "=f"(d[12]), "=f"(d[13]), "=f"(d[14]), "=f"(d[15]), "=f"(d[16]), "=f"(d[17]), "=f"(d[18]), "=f"(d[19]), "=f"(d[20]), "=f"(d[21]), "=f"(d[22]), "=f"(d[23]), "=f"(d[24]), "=f"(d[25]), "=f"(d[26]), "=f"(d[27]), "=f"(d[28]), "=f"(d[29]), "=f"(d[30]), "=f"(d[31]), "=f"(d[32]), "=f"(d[33]), "=f"(d[34]), "=f"(d[35]), "=f"(d[36]), "=f"(d[37]), "=f"(d[38]), "=f"(d[39]), "=f"(d[40]), "=f"(d[41]), "=f"(d[42]), "=f"(d[43]), "=f"(d[44]), "=f"(d[45]), "=f"(d[46]), "=f"(d[47]), "=f"(d[48]), "=f"(d[49]), "=f"(d[50]), "=f"(d[51]), "=f"(d[52]), "=f"(d[53]), "=f"(d[54]), "=f"(d[55]), "=f"(d[56]), "=f"(d[57]), "=f"(d[58]), "=f"(d[59]), "=f"(d[60]), "=f"(d[61]), "=f"(d[62]), "=f"(d[63]), "=f"(d[64]), "=f"(d[65]), "=f"(d[66]), "=f"(d[67]), "=f"(d[68]), "=f"(d[69]), "=f"(d[70]), "=f"(d[71]), "=f"(d[72]), "=f"(d[73]), "=f"(d[74]), "=f"(d[75]), "=f"(d[76]), "=f"(d[77]), "=f"(d[78]), "=f"(d[79]), "=f"(d[80]), "=f"(d[81]), "=f"(d[82]), "=f"(d[83]), "=f"(d[84]), "=f"(d[85]), "=f"(d[86]), "=f"(d[87]), "=f"(d[88]), "=f"(d[89]), "=f"(d[90]), "=f"(d[91]), "=f"(d[92]), "=f"(d[93]), "=f"(d[94]), "=f"(d[95]), "=f"(d[96]), "=f"(d[97]), "=f"(d[98]), "=f"(d[99]), "=f"(d[100]), "=f"(d[101]), "=f"(d[102]), "=f"(d[103]), "=f"(d[104]), "=f"(d[105]), "=f"(d[106]), "=f"(d[107]), "=f"(d[108]), "=f"(d[109]), "=f"(d[110]), "=f"(d[111]), "=f"(d[112]), "=f"(d[113]), "=f"(d[114]), "=f"(d[115]), "=f"(d[116]), "=f"(d[117]), "=f"(d[118]), "=f"(d[119]), "=f"(d[120]), "=f"(d[121]), "=f"(d[122]), "=f"(d[123]), "=f"(d[124]), "=f"(d[125]), "=f"(d[126]), "=f"(d[127])
    : "l"(da), "l"(db));
}

template <int OFF, int IMM>
__device__ __forceinline__ void wgmma_sp_n128_init(float (&d)[128], const uint32_t* a, uint32_t base, uint32_t meta) {
  asm volatile(
    "{\n.reg .b32 lo;\n.reg .b64 db;\nadd.u32 lo, %68, %70;\nmov.b64 db, {lo, 0x40000040};\n"
    "wgmma.mma_async.sp.sync.aligned.m64n128k32.f32.bf16.bf16 {%0, %1, %2, %3, %4, %5, %6, %7, %8, %9, %10, %11, %12, %13, %14, %15, %16, %17, %18, %19, %20, %21, %22, %23, %24, %25, %26, %27, %28, %29, %30, %31, %32, %33, %34, %35, %36, %37, %38, %39, %40, %41, %42, %43, %44, %45, %46, %47, %48, %49, %50, %51, %52, %53, %54, %55, %56, %57, %58, %59, %60, %61, %62, %63}, {%64, %65, %66, %67}, db, %69, 0, 0, 1, 1, 1;\n}\n"
    : "=f"(d[OFF + 0]), "=f"(d[OFF + 1]), "=f"(d[OFF + 2]), "=f"(d[OFF + 3]), "=f"(d[OFF + 4]), "=f"(d[OFF + 5]), "=f"(d[OFF + 6]), "=f"(d[OFF + 7]), "=f"(d[OFF + 8]), "=f"(d[OFF + 9]), "=f"(d[OFF + 10]), "=f"(d[OFF + 11]), "=f"(d[OFF + 12]), "=f"(d[OFF + 13]), "=f"(d[OFF + 14]), "=f"(d[OFF + 15]), "=f"(d[OFF + 16]), "=f"(d[OFF + 17]), "=f"(d[OFF + 18]), "=f"(d[OFF + 19]), "=f"(d[OFF + 20]), "=f"(d[OFF + 21]), "=f"(d[OFF + 22]), "=f"(d[OFF + 23]), "=f"(d[OFF + 24]), "=f"(d[OFF + 25]), "=f"(d[OFF + 26]), "=f"(d[OFF + 27]), "=f"(d[OFF + 28]), "=f"(d[OFF + 29]), "=f"(d[OFF + 30]), "=f"(d[OFF + 31]), "=f"(d[OFF + 32]), "=f"(d[OFF + 33]), "=f"(d[OFF + 34]), "=f"(d[OFF + 35]), "=f"(d[OFF + 36]), "=f"(d[OFF + 37]), "=f"(d[OFF + 38]), "=f"(d[OFF + 39]), "=f"(d[OFF + 40]), "=f"(d[OFF + 41]), "=f"(d[OFF + 42]), "=f"(d[OFF + 43]), "=f"(d[OFF + 44]), "=f"(d[OFF + 45]), "=f"(d[OFF + 46]), "=f"(d[OFF + 47]), "=f"(d[OFF + 48]), "=f"(d[OFF + 49]), "=f"(d[OFF + 50]), "=f"(d[OFF + 51]), "=f"(d[OFF + 52]), "=f"(d[OFF + 53]), "=f"(d[OFF + 54]), "=f"(d[OFF + 55]), "=f"(d[OFF + 56]), "=f"(d[OFF + 57]), "=f"(d[OFF + 58]), "=f"(d[OFF + 59]), "=f"(d[OFF + 60]), "=f"(d[OFF + 61]), "=f"(d[OFF + 62]), "=f"(d[OFF + 63])
    : "r"(a[0]), "r"(a[1]), "r"(a[2]), "r"(a[3]), "r"(base), "r"(meta), "n"(IMM));
}

template <int TB, int OFF, int IMM>
__device__ __forceinline__ void wgmma_rs_n64_init(float (&d)[128], const uint32_t* a, uint32_t base) {
  asm volatile(
    "{\n.reg .b32 lo;\n.reg .b64 db;\nadd.u32 lo, %36, %38;\nmov.b64 db, {lo, 0x40000040};\n"
    "wgmma.mma_async.sync.aligned.m64n64k16.f32.bf16.bf16 {%0, %1, %2, %3, %4, %5, %6, %7, %8, %9, %10, %11, %12, %13, %14, %15, %16, %17, %18, %19, %20, %21, %22, %23, %24, %25, %26, %27, %28, %29, %30, %31}, {%32, %33, %34, %35}, db, 0, 1, 1, %37;\n}\n"
    : "=f"(d[OFF + 0]), "=f"(d[OFF + 1]), "=f"(d[OFF + 2]), "=f"(d[OFF + 3]), "=f"(d[OFF + 4]), "=f"(d[OFF + 5]), "=f"(d[OFF + 6]), "=f"(d[OFF + 7]), "=f"(d[OFF + 8]), "=f"(d[OFF + 9]), "=f"(d[OFF + 10]), "=f"(d[OFF + 11]), "=f"(d[OFF + 12]), "=f"(d[OFF + 13]), "=f"(d[OFF + 14]), "=f"(d[OFF + 15]), "=f"(d[OFF + 16]), "=f"(d[OFF + 17]), "=f"(d[OFF + 18]), "=f"(d[OFF + 19]), "=f"(d[OFF + 20]), "=f"(d[OFF + 21]), "=f"(d[OFF + 22]), "=f"(d[OFF + 23]), "=f"(d[OFF + 24]), "=f"(d[OFF + 25]), "=f"(d[OFF + 26]), "=f"(d[OFF + 27]), "=f"(d[OFF + 28]), "=f"(d[OFF + 29]), "=f"(d[OFF + 30]), "=f"(d[OFF + 31])
    : "r"(a[0]), "r"(a[1]), "r"(a[2]), "r"(a[3]), "r"(base), "n"(TB), "n"(IMM));
}

template <int OFF, bool INIT, int IMM>
__device__ __forceinline__ void g2_group(float (&d)[128], const uint32_t* a, uint32_t base) {
  if (INIT) wgmma_rs_n64_init<1, OFF, IMM>(d, a, base);
  else wgmma_rs_n64<1, OFF, IMM>(d, a, base);
  wgmma_rs_n64<1, OFF, IMM + 128>(d, a + 4, base);
  wgmma_rs_n64<1, OFF, IMM + 256>(d, a + 8, base);
  wgmma_rs_n64<1, OFF, IMM + 384>(d, a + 12, base);
  wgmma_rs_n64<1, OFF, IMM + 512>(d, a + 16, base);
  wgmma_rs_n64<1, OFF, IMM + 640>(d, a + 20, base);
  wgmma_rs_n64<1, OFF, IMM + 768>(d, a + 24, base);
  wgmma_rs_n64<1, OFF, IMM + 896>(d, a + 28, base);
}

template <int OFF, int IMM, int B, int E>
__device__ __forceinline__ void g2_part(float (&d)[128], const uint32_t* a, uint32_t base) {
  if constexpr (B < E) {
    wgmma_rs_n64<1, OFF, IMM + 128 * B>(d, a + 4 * B, base);
    g2_part<OFF, IMM, B + 1, E>(d, a, base);
  }
}
template <int I>
struct IC { static constexpr int value = I; };
template <int B, int E, class F>
__device__ __forceinline__ void static_for(F&& f) {
  if constexpr (B < E) {
    f(IC<B>{});
    static_for<B + 1, E>(f);
  }
}

__host__ __device__ constexpr int xslot(int k) { return (k & 1) ? 4 + (k >> 1) : (k >> 1); }
enum { K_V0, K_K1, K_V1, K_WI, K_W };
__host__ __device__ constexpr int n_kind(int n) {
  constexpr int t[16] = {K_V0, K_V0, K_WI, K_WI, K_V0, K_V0, K_WI, K_WI, K_K1, K_K1, K_V1, K_V1, K_K1, K_K1, K_V1, K_V1};
  return n < 16 ? t[n] : K_W;
}
__host__ __device__ constexpr int n_a(int n) {
  constexpr int t[16] = {0, 0, 0, 1, 1, 1, 2, 3, 0, 0, 0, 0, 1, 1, 1, 1};
  return n < 16 ? t[n] : n - 16;
}
__host__ __device__ constexpr int n_b(int n) {
  constexpr int t[16] = {0, 1, 0, 0, 0, 1, 0, 0, 0, 1, 0, 1, 0, 1, 0, 1};
  return n < 16 ? t[n] : 0;
}
__host__ __device__ constexpr int item_slot(int it) {
  constexpr int t[16] = {7, 8, 9, 10, 11, 12, 13, 3, 0, 1, 7, 8, 4, 5, 11, 12};
  constexpr int ws[12] = {9, 10, 13, 0, 1, 3, 7, 8, 4, 5, 11, 12};
  return it < 28 ? 7 + it % 7 : (it < 44 ? t[it - 28] : ws[(it - 44) % 12]);
}
__host__ __device__ constexpr int item_wait(int it) {
  constexpr int t[24] = {B_XEMPTY + 6, B_XEMPTY + 7, B_XEMPTY + 7, B_EMPTY + 28, B_EMPTY + 29, B_XEMPTY + 8, B_XEMPTY + 8,
                         B_EMPTY + 32, B_EMPTY + 33,
                         B_EMPTY + 30, B_EMPTY + 31, B_EMPTY + 34, B_EMPTY + 36, B_EMPTY + 37, B_EMPTY + 35, B_EMPTY + 38,
                         B_EMPTY + 39, B_EMPTY + 40, B_EMPTY + 41, B_EMPTY + 42, B_EMPTY + 43};
  return it < 35 ? B_EMPTY + it - 7 : (it < 56 ? t[it - 35] : B_EMPTY + it - 12);
}
__host__ __device__ constexpr int find_item(int kind, int a, int b) {
  for (int n = 0; n < 40; n++)
    if (n_kind(n) == kind && n_a(n) == a && n_b(n) == b) return 28 + n;
  return -1;
}
__host__ __device__ constexpr bool slot_reused(int it) { return it + 12 < NITEMS; }
__host__ __device__ constexpr int w_step(int g) { return g < 2 ? 2 : (g < 6 ? (g - 2) >> 1 : 2 + ((g - 4) >> 2)); }
__host__ __device__ constexpr int w_kq(int g) { return g < 2 ? g : (g < 6 ? 2 + (g & 1) : (g - 4) & 3); }
__host__ __device__ constexpr int w_off(int s) { return s == 2 ? 64 : (s < 2 ? 32 * s : 0); }

__device__ __forceinline__ int step_atom(int hg, int t) {
  if (t == 6) return min(hg, 6);
  int a = hg < 7 ? hg + 1 + t : 3 + t;
  const int m = hg < 7 ? 7 : 6;
  return a >= m ? a - m : a;
}
template <int OFF>
__device__ __forceinline__ void pack_tile(float (&acc)[128], uint32_t (&p)[16]) {
  acc_fence<OFF, 32>(acc);
#pragma unroll
  for (int i = 0; i < 16; i++) p[i] = pack_bf16(acc[OFF + 2 * i], acc[OFF + 2 * i + 1]);
}
template <int OFF>
__device__ __forceinline__ void epi_stash(float (&acc)[128], uint32_t addr) {
  uint32_t p[16];
  pack_tile<OFF>(acc, p);
#pragma unroll
  for (int q = 0; q < 4; q++)
    asm volatile("st.shared.v4.b32 [%0], {%1, %2, %3, %4};" ::"r"(addr + q * 512), "r"(p[4 * q]), "r"(p[4 * q + 1]),
                 "r"(p[4 * q + 2]), "r"(p[4 * q + 3])
                 : "memory");
}
__device__ __forceinline__ void tile_lds(uint32_t (&p)[16], uint32_t addr) {
#pragma unroll
  for (int q = 0; q < 4; q++)
    asm volatile("ld.shared.v4.b32 {%0, %1, %2, %3}, [%4];"
                 : "=r"(p[4 * q]), "=r"(p[4 * q + 1]), "=r"(p[4 * q + 2]), "=r"(p[4 * q + 3])
                 : "r"(addr + q * 512)
                 : "memory");
}
__device__ __forceinline__ void tile_ldg(uint32_t (&p)[16], const unsigned char* src, uint32_t l16) {
  ld_pkt2(src, l16, &p[0]);
  ld_pkt2(src, l16 + 1024u, &p[8]);
}
template <int OFF, bool ADD>
__device__ __forceinline__ void tile_acc(float (&acc)[128], uint32_t (&p)[16]) {
#pragma unroll
  for (int i = 0; i < 16; i++) {
    acc[OFF + 2 * i] = ADD ? acc[OFF + 2 * i] + bf_lo(p[i]) : bf_lo(p[i]);
    acc[OFF + 2 * i + 1] = ADD ? acc[OFF + 2 * i + 1] + bf_hi(p[i]) : bf_hi(p[i]);
  }
}
template <int OFF>
__device__ __forceinline__ void epi_store(float (&acc)[128], unsigned char* dst, uint32_t par, uint32_t l16) {
  uint32_t p[16];
  pack_tile<OFF>(acc, p);
#pragma unroll
  for (int q = 0; q < 4; q++)
    st_pkt(dst + q * 512, l16, (p[4 * q] & ~1u) | par, p[4 * q + 1], p[4 * q + 2], p[4 * q + 3]);
}
__device__ __forceinline__ void tile_validate(uint32_t (&p)[16], const unsigned char* src, uint32_t par, uint32_t l16) {
  int spins = 0;
  while (__any_sync(0xffffffffu, ((p[0] ^ par) | (p[4] ^ par) | (p[8] ^ par) | (p[12] ^ par)) & 1u) &&
         ++spins < (1 << 18)) {
    tile_ldg(p, src, l16);
  }
}

__global__ void __launch_bounds__(384, 1) fused_attn_kernel(const __grid_constant__ Params prm) {
  extern __shared__ unsigned char smem_raw[];
  const uint32_t sbase = (smem_u32(smem_raw) + 1023) & ~1023u;
  const uint32_t bars = sbase + NSLOT * SLOT;

  const int tid = threadIdx.x;
  const int warp = __shfl_sync(0xffffffffu, tid >> 5, 0), lane = tid & 31;
  const int bid = blockIdx.x;
  const int rb = bid & 7, br = (bid >> 3) & 1, hg = bid >> 4;
  const int grp = br * 8 + rb;
  const int rsw = hg == 7;
  const int hd0 = 2 * hg, hd1 = 2 * hg + 1;
  const CUtensorMap* maps = &prm.maps[br * 5];

  if (warp == 8) {
    if (lane == 0) {
      mbar_init(bars + 8 * B_FULL, 1);
      mbar_init(bars + 8 * B_XFULL, 1);
      mbar_expect(bars + 8 * B_FULL, SLOT);
      tma_3d(sbase + 7 * SLOT, maps + 1, bars + 8 * B_FULL, 0, 0, 4 * hd1);
      mbar_expect(bars + 8 * B_XFULL, SLOT);
      tma_2d(sbase, maps + 0, bars + 8 * B_XFULL, 0, rb * 128);
#pragma unroll
      for (int i = 1; i < 7; i++) {
        mbar_init(bars + 8 * (B_XFULL + i), 1);
        mbar_init(bars + 8 * (B_FULL + i), 1);
      }
    }
    __syncwarp();
    asm volatile("bar.arrive 0, 384;" ::: "memory");
    if (lane == 0) {
#pragma unroll
      for (int i = 1; i < 7; i++) {
        mbar_expect(bars + 8 * (B_FULL + i), SLOT);
        tma_3d(sbase + (7 + i) * SLOT, maps + 1, bars + 8 * (B_FULL + i), 0, 32 * i, 4 * hd1);
        if (!(i & 1)) {
          const int k = i >> 1;
          mbar_expect(bars + 8 * (B_XFULL + k), SLOT);
          tma_2d(sbase + xslot(k) * SLOT, maps + 0, bars + 8 * (B_XFULL + k), 64 * k, rb * 128);
        }
      }
    }
    __syncwarp();
  }
  if (warp >= 8) {
    asm volatile("setmaxnreg.dec.sync.aligned.u32 24;");
    if (warp != 8) {
      if (warp == 9 && lane == 0) {
#pragma unroll
        for (int i = 0; i < 10; i++) mbar_init(bars + 8 * (B_GATE + i), 4);
      }
      if (warp == 10 && lane == 0) {
        asm volatile("prefetch.tensormap [%0];" ::"l"((uint64_t)(maps + 2)) : "memory");
        asm volatile("prefetch.tensormap [%0];" ::"l"((uint64_t)(maps + 3)) : "memory");
        asm volatile("prefetch.tensormap [%0];" ::"l"((uint64_t)(maps + 4)) : "memory");
      }
      __syncwarp();
      asm volatile("bar.arrive 2, 384;" ::: "memory");
      asm volatile("bar.sync 0, 384;" ::: "memory");
    }
    if (warp == 8) {
      asm volatile("bar.sync 2, 384;" ::: "memory");
      if (lane == 0) {
        const int kv0 = br ? hd0 : hg, kv1 = br ? hd1 : hg, b0 = rb * 4;
        static_for<7, NITEMS>([&](auto IT) {
          constexpr int it = decltype(IT)::value;
          const uint32_t fb = bars + 8 * (B_FULL + it);
          const uint32_t dst = sbase + item_slot(it) * SLOT;
          if constexpr (it >= 36 && it < 44) {
            if (!br) {
              mbar_arrive(fb);
              return;
            }
          }
          mbar_wait(bars + 8 * item_wait(it));
          mbar_expect(fb, SLOT);
          if constexpr (it < 28) {
            constexpr int hh = it >= 14, pc = it - 14 * hh;
            tma_3d(dst, maps + 1, fb, 0, 32 * pc, 4 * (hh ? hd0 : hd1));
          } else {
            constexpr int kind = n_kind(it - 28), a = n_a(it - 28), b = n_b(it - 28);
            if constexpr (kind == K_V0 || kind == K_V1) {
              tma_5d(dst, maps + 3, fb, 0, 0, b0 + 2 * (a ^ rsw), 16 * (kind == K_V1 ? kv1 : kv0), 2 * b);
            } else if constexpr (kind == K_K1) {
              tma_5d(dst, maps + 2, fb, 0, 0, b0 + 2 * (a ^ rsw), 2 * b, kv1);
            } else {
              constexpr int step = kind == K_WI ? a >> 1 : w_step(a), kq = kind == K_WI ? a & 1 : w_kq(a);
              tma_2d(dst, maps + 4, fb, 64 * step_atom(hg, step), 256 * (kq < 2 ? hd0 : hd1) + 128 * (kq & 1));
            }
          }
          if constexpr (it == 7 || it == 9 || it == 11) {
            constexpr int k = 4 + (it - 7) / 2;
            mbar_expect(bars + 8 * (B_XFULL + k), SLOT);
            tma_2d(sbase + xslot(k) * SLOT, maps + 0, bars + 8 * (B_XFULL + k), 64 * k, rb * 128);
          }
          if constexpr (it >= 22 && it <= 28 && !(it & 1)) {
            constexpr int j = (it - 22) >> 1;
            mbar_wait(bars + 8 * (B_XEMPTY + j));
            mbar_expect(bars + 8 * (B_KFULL + j), SLOT);
            tma_5d(sbase + xslot(j) * SLOT, maps + 2, bars + 8 * (B_KFULL + j), 0, 0, b0 + 2 * ((j & 1) ^ rsw), 2 * (j >> 1), kv0);
          }
        });
      }
      __syncwarp();
    } else {
      if (warp >= 10) {
        const int H = br ? 16 : 8;
        const unsigned char* wq = prm.ptr[br * 5 + 3] + hg * 1024;
        const unsigned char* wo = prm.ptr[br * 5 + 4] + (size_t)(hg * 512) * 896;
        auto addr = [&](int b) -> const unsigned char* {
          if (b < 6) {
            int idx = b * 32 + lane;
            if (idx >= 168) idx = 167;
            if (idx < 112) return wq + (size_t)(224 + rb + 8 * (idx >> 2)) * 8192 + (idx & 3) * 256;
            idx -= 112;
            return wq + (size_t)(rb + 8 * (idx >> 1)) * 8192 + (idx & 1) * 256;
          }
          if (b < 22) {
            const int x = b - 6;
            return prm.ptr[br * 5 + 1 + (x >> 3)] + (size_t)((rb * 4 + ((x >> 1) & 3)) * H + (br ? hd0 : hg)) * 16384 +
                   (x & 1) * 8192 + lane * 256;
          }
          if (b < 24) return wo + (rb * 32 + lane) * 896 + step_atom(hg, b - 22) * 128;
          if (b < 32) {
            const int x = b - 24;
            return prm.ptr[6 + (x >> 2)] + (size_t)((rb * 4 + (x & 3)) * 16 + hd1) * 16384 + br * 8192 + lane * 256;
          }
          return wo + (min(b - 32, 6) * 8 + rb) * 8192 + lane * 256;
        };
        mbar_wait(bars + 8 * (B_FULL + 2));
        uint32_t sink = 0, pf0 = 0, pf1 = 0;
#pragma unroll 1
        for (int b = warp - 10; b < 40; b += 4) {
          const unsigned char* p0 = addr(b);
          sink ^= pf0;
          pf0 = ld_pf(p0);
          const unsigned char* p1 = addr(min(b + 2, 39));
          sink ^= pf1;
          pf1 = ld_pf(p1);
        }
        asm volatile("st.shared.u32 [%0], %1;" ::"r"(bars + 8 * B_SINK), "r"(sink) : "memory");
      }
      if (warp >= 10 && lane == 0 && (hg < 6 || warp == 11)) {
        const int w = warp - 10;
        const unsigned char* src = g_part + (size_t)grp * GRP_BYTES + min(hg, 6) * (6 * BOX) + (w ^ rsw) * 8192;
#pragma unroll 1
        for (int u = 0; u < 5; u++) {
          mbar_wait(bars + 8 * (B_GATE + 2 * u + w));
          mbar_expect(bars + 8 * (B_INB + 2 * u + w), 8192);
          asm volatile("cp.async.bulk.shared::cluster.global.mbarrier::complete_tx::bytes [%0], [%1], 8192, [%2];" ::"r"(
                           sbase + (2 + 4 * w) * SLOT + (u & 1) * 8192),
                       "l"(src + u * BOX), "r"(bars + 8 * (B_INB + 2 * u + w))
                       : "memory");
        }
      }
    }
  } else {
    if (lane == 0) {
#pragma unroll
      for (int i = 0; i < 11; i++) mbar_init(bars + 8 * (14 + 11 * warp + i), 1);
#pragma unroll
      for (int i = 0; i < 9; i++) mbar_init(bars + 8 * (B_EMPTY + 9 * warp + i), 8);
    }
    __syncwarp();
    asm volatile("bar.arrive 2, 384;" ::: "memory");
    asm volatile("bar.sync 0, 384;" ::: "memory");
    const int w = warp >> 2;
    float acc[128];
    uint32_t qf0[64], qf1[64];
    uint32_t par;
    asm volatile("ld.relaxed.gpu.global.u32 %0, [%1];" : "=r"(par) : "l"(&g_epoch[bid * 8]) : "memory");
    const int rwarp = warp ^ (4 * rsw);
    unsigned char* gbase = g_part + (size_t)grp * GRP_BYTES + rwarp * TILE;
    const uint32_t l16 = lane * 16;

    int slot = 0, it = 0;
#pragma unroll
    for (int hh = 0; hh < 2; hh++) {
      {
        if (hh == 0) mbar_wait(bars + 8 * B_XFULL);
        mbar_wait(bars + 8 * (B_FULL + it));
        const uint64_t da = make_desc(sbase + (w ^ rsw) * 8192, 16, 1024);
        const uint64_t db = make_desc(sbase + (7 + slot) * SLOT, 4096, 1024);
        wg_fence();
        wgmma_ss_n256_init(acc, da, db);
        wgmma_ss_n256(acc, da + 2, db + 128);
        wg_commit();
        it++;
        if (++slot == 7) slot = 0;
      }
#pragma unroll 1
      for (int i = 1; i < 14; i++) {
        const int xs = xslot(i >> 1);
        if (hh == 0 && (i & 1) == 0) mbar_wait(bars + 8 * (B_XFULL + (i >> 1)));
        if (hh == 1 && i == 10 && w == 1) asm volatile("bar.sync 3, 256;" ::: "memory");
        mbar_wait(bars + 8 * (B_FULL + it));
        const uint64_t da = make_desc(sbase + xs * SLOT + (w ^ rsw) * 8192 + (i & 1) * 64, 16, 1024);
        const uint64_t db = make_desc(sbase + (7 + slot) * SLOT, 4096, 1024);
        wg_fence();
        wgmma_ss_n256(acc, da, db);
        wgmma_ss_n256(acc, da + 2, db + 128);
        wg_commit();
        if (hh == 1 && i == 13 && w == 0) asm volatile("bar.arrive 3, 256;" ::: "memory");
        wg_wait<1>();
        if (lane == 0) {
          mbar_arrive(bars + 8 * (B_EMPTY + it - 1));
          if (hh == 1 && (i & 1) == 0) mbar_arrive(bars + 8 * (B_XEMPTY + (i >> 1) - 1));
        }
        it++;
        if (++slot == 7) slot = 0;
      }
      if (hh == 0) asm volatile("setmaxnreg.inc.sync.aligned.u32 240;");
      wg_wait<0>();
      acc_fence<0, 128>(acc);
      if (lane == 0) {
        mbar_arrive(bars + 8 * (B_EMPTY + it - 1));
        if (hh == 1) mbar_arrive(bars + 8 * (B_XEMPTY + 6));
      }
#pragma unroll
      for (int i = 0; i < 64; i++) {
        if (hh == 0) qf1[i] = pack_bf16(acc[2 * i], acc[2 * i + 1]);
        else qf0[i] = pack_bf16(acc[2 * i], acc[2 * i + 1]);
      }
    }
    {
      const uint32_t t = qf0[62] & qf0[63] & blockIdx.y;
#pragma unroll
      for (int i = 0; i < 8; i++) qf0[i] ^= t;
    }
    const uint32_t epoch = __shfl_sync(0xffffffffu, par, 0) + 1;
    par = epoch & 1;

    const int jb = (warp >> 1) & 1;
    const uint32_t meta = jb ? 0xEEEEEEEEu : 0x44444444u;
    const uint32_t ustash = sbase + (2 + 4 * w) * SLOT + (warp & 3) * 2048;
#define stash (ustash + l16)
    uint32_t of0[64], of1[64];
    const uint32_t sb16 = (sbase & 0x3FFFF) >> 4;

    auto s_issue = [&](uint32_t(&q)[64], uint32_t bar_a, uint32_t bar_b, uint32_t slot_a, uint32_t slot_b) {
      mbar_wait(bar_a);
      {
        const uint32_t kb = sb16 + slot_a * 1024;
        wg_fence();
        wgmma_rs_n64_init<0, 0, 0x10000>(acc, &q[0], kb);
        static_for<1, 8>([&](auto S) {
          constexpr int s = decltype(S)::value;
          wgmma_rs_n64<0, 0, 0x10000 + (s >> 2) * 512 + (s & 3) * 2>(acc, &q[4 * s], kb);
        });
      }
      mbar_wait(bar_b);
      {
        const uint32_t kb = sb16 + slot_b * 1024;
        wg_fence();
        static_for<0, 8>([&](auto S) {
          constexpr int s = decltype(S)::value;
          wgmma_rs_n64<0, 0, 0x10000 + (s >> 2) * 512 + (s & 3) * 2>(acc, &q[32 + 4 * s], kb);
        });
      }
      wg_commit();
    };
    auto softmax_pv = [&](uint32_t(&o)[64], int ita, int itb, int slot_a, int slot_b) {
      uint32_t pf[8];
      float v[16];
#pragma unroll
      for (int i = 0; i < 16; i += 2) {
        const uint32_t r = pack_bf16(jb ? acc[16 + i] : acc[i], jb ? acc[17 + i] : acc[i + 1]);
        v[i] = bf_lo(r);
        v[i + 1] = bf_hi(r);
      }
      float m0 = fmaxf(fmaxf(fmaxf(v[0], v[1]), fmaxf(v[4], v[5])), fmaxf(fmaxf(v[8], v[9]), fmaxf(v[12], v[13])));
      float m1 = fmaxf(fmaxf(fmaxf(v[2], v[3]), fmaxf(v[6], v[7])), fmaxf(fmaxf(v[10], v[11]), fmaxf(v[14], v[15])));
      m0 = fmaxf(m0, __shfl_xor_sync(0xffffffffu, m0, 1));
      m1 = fmaxf(m1, __shfl_xor_sync(0xffffffffu, m1, 1));
      m0 = fmaxf(m0, __shfl_xor_sync(0xffffffffu, m0, 2));
      m1 = fmaxf(m1, __shfl_xor_sync(0xffffffffu, m1, 2));
      const float sc = 0.0625f * 1.4426950408889634f;
#pragma unroll
      for (int jj = 0; jj < 4; jj++) {
        v[4 * jj] = ex2((v[4 * jj] - m0) * sc);
        v[4 * jj + 1] = ex2((v[4 * jj + 1] - m0) * sc);
        v[4 * jj + 2] = ex2((v[4 * jj + 2] - m1) * sc);
        v[4 * jj + 3] = ex2((v[4 * jj + 3] - m1) * sc);
      }
      float s0 = ((v[0] + v[1]) + (v[4] + v[5])) + ((v[8] + v[9]) + (v[12] + v[13]));
      float s1 = ((v[2] + v[3]) + (v[6] + v[7])) + ((v[10] + v[11]) + (v[14] + v[15]));
      s0 += __shfl_xor_sync(0xffffffffu, s0, 1);
      s1 += __shfl_xor_sync(0xffffffffu, s1, 1);
      s0 += __shfl_xor_sync(0xffffffffu, s0, 2);
      s1 += __shfl_xor_sync(0xffffffffu, s1, 2);
      const float r0 = rcp(s0), r1 = rcp(s1);
#pragma unroll
      for (int jj = 0; jj < 4; jj++) {
        pf[2 * jj] = pack_bf16(v[4 * jj] * r0, v[4 * jj + 1] * r0);
        pf[2 * jj + 1] = pack_bf16(v[4 * jj + 2] * r1, v[4 * jj + 3] * r1);
      }
      mbar_wait(bars + 8 * (B_FULL + ita));
      {
        const uint32_t vb = sb16 + slot_a * 1024;
        wg_fence();
        wgmma_sp_n128_init<0, 0x2000000>(acc, &pf[0], vb, meta);
        wgmma_sp_n128<0, 0x2000000 + 256>(acc, &pf[4], vb, meta);
        wg_commit();
      }
      mbar_wait(bars + 8 * (B_FULL + itb));
      {
        const uint32_t vb = sb16 + slot_b * 1024;
        wg_fence();
        wgmma_sp_n128_init<64, 0x2000000>(acc, &pf[0], vb, meta);
        wgmma_sp_n128<64, 0x2000000 + 256>(acc, &pf[4], vb, meta);
      }
      wg_commit();
      wg_wait<1>();
      acc_fence<0, 64>(acc);
#pragma unroll
      for (int i = 0; i < 32; i++) o[i] = pack_bf16(acc[2 * i], acc[2 * i + 1]);
#pragma unroll
      for (int i = 0; i < 32; i++) asm volatile("" : "+r"(o[i])::"memory");
      wg_wait<0>();
      acc_fence<64, 64>(acc);
      if (lane == 0) {
        mbar_arrive2(bars + 8 * (B_EMPTY + ita));
        mbar_arrive2(bars + 8 * (B_EMPTY + itb));
      }
#pragma unroll
      for (int i = 32; i < 64; i++) o[i] = pack_bf16(acc[2 * i], acc[2 * i + 1]);
    };
#define SEL_IT(kind, b) (w ? find_item(kind, 1, b) : find_item(kind, 0, b))
#define SEL_SLOT(kind, b) (w ? item_slot(find_item(kind, 1, b)) : item_slot(find_item(kind, 0, b)))

    s_issue(qf0, bars + 8 * (B_KFULL + w), bars + 8 * (B_KFULL + 2 + w), 4 * w, 4 * w + 1);
    wg_wait<0>();
    acc_fence<0, 32>(acc);
    if (lane == 0) mbar_arrive2(bars + 8 * (B_XEMPTY + 7 + w));
    softmax_pv(qf0, SEL_IT(K_V0, 0), SEL_IT(K_V0, 1), SEL_SLOT(K_V0, 0), SEL_SLOT(K_V0, 1));

    static_for<0, 4>([&](auto G) {
      constexpr int g = decltype(G)::value, c = g >> 1, kq = g & 1, it2 = find_item(K_WI, g, 0);
      mbar_wait(bars + 8 * (B_FULL + it2));
      wg_fence();
      g2_group<32 * (c & 1), kq == 0, 0x2000000 + item_slot(it2) * 1024>(acc, &qf0[32 * kq], sb16);
      wg_commit();
      if constexpr (g > 0) {
        wg_wait<1>();
        if (lane == 0) mbar_arrive(bars + 8 * (B_EMPTY + find_item(K_WI, g - 1, 0)));
      }
      if constexpr (g == 2) {
        mbar_wait(bars + 8 * (B_XEMPTY + 4 + w));
        epi_stash<0>(acc, stash);
      }
    });
    s_issue(qf1, bars + 8 * (B_FULL + SEL_IT(K_K1, 0)), bars + 8 * (B_FULL + SEL_IT(K_K1, 1)), SEL_SLOT(K_K1, 0),
            SEL_SLOT(K_K1, 1));
    wg_wait<1>();
    if (lane == 0) mbar_arrive(bars + 8 * (B_EMPTY + find_item(K_WI, 3, 0)));
    epi_stash<32>(acc, stash + 8192);
    wg_wait<0>();
    acc_fence<0, 32>(acc);
    if (lane == 0) {
      mbar_arrive2(bars + 8 * (B_EMPTY + SEL_IT(K_K1, 0)));
      mbar_arrive2(bars + 8 * (B_EMPTY + SEL_IT(K_K1, 1)));
    }
    {
      const uint32_t z = blockIdx.y;
#pragma unroll
      for (int i = 0; i < 64; i++) of0[i] = qf0[i] ^ z;
    }
    softmax_pv(of1, SEL_IT(K_V1, 0), SEL_IT(K_V1, 1), SEL_SLOT(K_V1, 0), SEL_SLOT(K_V1, 1));

    const unsigned char* inbox = gbase + min(hg, 6) * (6 * BOX);
    const unsigned char* inbox_x = gbase + (42 + min(hg, 6)) * BOX;
    const bool owner = hg < 6 || w == 1;
    uint32_t pk[16], pl[16];
    const bool early = w == 1, early_x = early && hg < 6 && hg != 2;
    auto ask = [&](int u) {
      if (lane == 0) mbar_arrive(bars + 8 * (B_GATE + 2 * u + w));
    };
    auto fold = [&](auto U) {
      constexpr int u = decltype(U)::value;
      if (owner) {
        mbar_wait(bars + 8 * (B_INB + 2 * u + w));
        tile_lds(pk, stash + (u & 1) * 8192);
        tile_validate(pk, inbox + u * BOX, par, l16);
        tile_acc<64, true>(acc, pk);
      }
    };
    auto mail = [&](auto S) {
      constexpr int s = decltype(S)::value;
      const int a = step_atom(hg, s);
      epi_store<w_off(s)>(acc, gbase + (hg < 7 ? a * 6 + s : 42 + a) * BOX, par, l16);
    };
    static_for<0, 20>([&](auto G) {
      constexpr int g = decltype(G)::value, s = w_step(g), kq = w_kq(g), it2 = find_item(K_W, g, 0), OFF = w_off(s);
      mbar_wait(bars + 8 * (B_FULL + it2));
      if constexpr (g >= 2 && (g == 2 || w_kq(g - 1) == 3))
        if (g > 2 || w == 1) asm volatile("bar.sync %0, 256;" ::"r"(4 + w) : "memory");
      wg_fence();
      if constexpr (kq == 3) {
        g2_part<OFF, 0x2000000 + item_slot(it2) * 1024, 0, 7>(acc, &of1[32], sb16);
        asm volatile("bar.arrive %0, 256;" ::"r"(5 - w) : "memory");
        g2_part<OFF, 0x2000000 + item_slot(it2) * 1024, 7, 8>(acc, &of1[32], sb16);
      } else {
        g2_group<OFF, kq == 0, 0x2000000 + item_slot(it2) * 1024>(acc, kq < 2 ? &of0[32 * (kq & 1)] : &of1[32 * (kq & 1)],
                                                                  sb16);
      }
      wg_commit();
      if constexpr (g == 1) {
        tile_lds(pk, stash);
        tile_acc<0, false>(acc, pk);
      }
      if constexpr (g == 2) {
        tile_lds(pk, stash + 8192);
        tile_acc<32, false>(acc, pk);
      }
      if constexpr (s == 2 && kq == 3) ask(0);
      if constexpr (s == 3 && kq == 1) ask(1);
      if constexpr (s >= 4 && kq == 0) ask(s - 2);
      if constexpr (s == 5 && kq == 2) ask(4);
      if constexpr (s == 5 && kq == 0)
        if (tid == 0) g_epoch[bid * 8] = epoch;
      if constexpr (s == 5 && kq == 3)
        if (early_x) tile_ldg(pl, inbox_x, l16);
      if constexpr (kq == 3) {
        wg_wait<0>();
        if (lane == 0) {
          if constexpr (slot_reused(it2 - 1)) mbar_arrive(bars + 8 * (B_EMPTY + it2 - 1));
          if constexpr (slot_reused(it2)) mbar_arrive(bars + 8 * (B_EMPTY + it2));
        }
        mail(IC<s>{});
        if constexpr (s == 1)
          asm volatile("fence.proxy.async.shared::cta;" ::: "memory");
        if constexpr (s == 2) {
#pragma unroll
          for (int i = 0; i < 32; i++) acc[64 + i] = 0.f;
        }
        if constexpr (s == 3) fold(IC<0>{});
        if constexpr (s >= 3) fold(IC<s - 2>{});
      } else if constexpr (g > 0 && w_kq(g - 1) != 3) {
        wg_wait<1>();
        if constexpr (slot_reused(it2 - 1))
          if (lane == 0) mbar_arrive(bars + 8 * (B_EMPTY + it2 - 1));
      }
    });
    {
      if (early) fold(IC<4>{});
      if (early_x) {
        tile_validate(pl, inbox_x, par, l16);
        tile_acc<64, true>(acc, pl);
      }
      asm volatile("bar.sync %0, 256;" ::"r"(4 + w) : "memory");
      static_for<0, 4>([&](auto KQ) {
        constexpr int kq = decltype(KQ)::value, it2 = find_item(K_W, 20 + kq, 0);
        mbar_wait(bars + 8 * (B_FULL + it2));
        wg_fence();
        if constexpr (kq == 3) {
          g2_part<64, 0x2000000 + item_slot(it2) * 1024, 0, 7>(acc, &of1[32], sb16);
          if (w == 0) asm volatile("bar.arrive 5, 256;" ::: "memory");
          g2_part<64, 0x2000000 + item_slot(it2) * 1024, 7, 8>(acc, &of1[32], sb16);
        } else {
          g2_part<64, 0x2000000 + item_slot(it2) * 1024, 0, 8>(acc, kq < 2 ? &of0[32 * (kq & 1)] : &of1[0], sb16);
        }
        if constexpr (kq == 2) {
          if (owner) tile_ldg(pk, inbox + 5 * BOX, l16);
          if (owner && !early_x) tile_ldg(pl, inbox_x, l16);
        }
      });
      wg_commit();
      wg_wait<0>();
      if (owner) {
        acc_fence<64, 32>(acc);
        tile_validate(pk, inbox + 5 * BOX, par, l16);
        tile_acc<64, true>(acc, pk);
        if (!early) fold(IC<4>{});
        if (!early_x) {
          tile_validate(pl, inbox_x, par, l16);
          tile_acc<64, true>(acc, pl);
        }
        const int t = lane & 3;
        __nv_bfloat16* o =
            prm.out + (size_t)(rb * 128 + rwarp * 16 + (lane >> 2)) * 896 + br * 448 + 64 * min(hg, 6) + 8 * t;
#pragma unroll
        for (int m = 0; m < 2; m++) {
#pragma unroll
          for (int h = 0; h < 2; h++) {
            uint32_t x[4];
#pragma unroll
            for (int j = 0; j < 4; j++)
              x[j] = pack_bf16(acc[64 + 16 * m + 4 * j + 2 * h], acc[65 + 16 * m + 4 * j + 2 * h]);
            {
              const bool od = t & 1;
              const uint32_t r0 = __shfl_xor_sync(0xffffffffu, od ? x[0] : x[1], 1);
              const uint32_t r1 = __shfl_xor_sync(0xffffffffu, od ? x[2] : x[3], 1);
              if (od) { x[0] = r0; x[2] = r1; } else { x[1] = r0; x[3] = r1; }
            }
            {
              const bool hi = t & 2;
              const uint32_t r0 = __shfl_xor_sync(0xffffffffu, hi ? x[0] : x[2], 2);
              const uint32_t r1 = __shfl_xor_sync(0xffffffffu, hi ? x[1] : x[3], 2);
              if (hi) { x[0] = r0; x[1] = r1; } else { x[2] = r0; x[3] = r1; }
            }
            *reinterpret_cast<uint4*>(o + h * 8 * 896 + 32 * m) = make_uint4(x[0], x[1], x[2], x[3]);
          }
        }
      } else {
        epi_store<64>(acc, gbase + 48 * BOX, par, l16);
      }
    }
  }
}

typedef CUresult (*EncodeFn)(CUtensorMap*, CUtensorMapDataType, cuuint32_t, void*, const cuuint64_t*, const cuuint64_t*,
                             const cuuint32_t*, const cuuint32_t*, CUtensorMapInterleave, CUtensorMapSwizzle,
                             CUtensorMapL2promotion, CUtensorMapFloatOOBfill);

void encode(EncodeFn fn, CUtensorMap* m, int rank, const void* ptr, const cuuint64_t* dims, const cuuint64_t* strides,
            const cuuint32_t* box) {
  cuuint32_t es[5] = {1, 1, 1, 1, 1};
  fn(m, CU_TENSOR_MAP_DATA_TYPE_BFLOAT16, rank, const_cast<void*>(ptr), dims, strides, box, es,
     CU_TENSOR_MAP_INTERLEAVE_NONE, CU_TENSOR_MAP_SWIZZLE_128B, CU_TENSOR_MAP_L2_PROMOTION_L2_256B,
     CU_TENSOR_MAP_FLOAT_OOB_FILL_NONE);
}

}

extern "C" void kernel_launch(void* const* d_in, const int* in_sizes, int n_in, void* d_out, int out_size) {
  (void)in_sizes; (void)n_in; (void)out_size;
  void* fnp = nullptr;
  cudaDriverEntryPointQueryResult qr;
  cudaGetDriverEntryPoint("cuTensorMapEncodeTiled", &fnp, cudaEnableDefault, &qr);
  EncodeFn fn = (EncodeFn)fnp;
  Params prm;
  for (int br = 0; br < 2; br++) {
    const void* x = d_in[br * 5 + 0];
    const void* kc = d_in[br * 5 + 1];
    const void* vc = d_in[br * 5 + 2];
    const void* wq = d_in[br * 5 + 3];
    const void* wo = d_in[br * 5 + 4];
    const cuuint64_t H = br ? 16 : 8;
    {
      cuuint64_t dims[2] = {448, 1024}, str[1] = {896};
      cuuint32_t box[2] = {64, 128};
      encode(fn, &prm.maps[br * 5 + 0], 2, x, dims, str, box);
    }
    {
      cuuint64_t dims[3] = {64, 448, 64}, str[2] = {8192, 128};
      cuuint32_t box[3] = {64, 32, 4};
      encode(fn, &prm.maps[br * 5 + 1], 3, wq, dims, str, box);
    }
    {
      cuuint64_t dims[5] = {64, 32, 32, 4, H}, str[4] = {512, H * 16384, 128, 16384};
      cuuint32_t box[5] = {64, 32, 2, 2, 1};
      encode(fn, &prm.maps[br * 5 + 2], 5, kc, dims, str, box);
    }
    {
      cuuint64_t dims[5] = {64, 2, 32, 16 * H, 4}, str[4] = {512, H * 16384, 1024, 128};
      cuuint32_t box[5] = {64, 2, 2, 16, 2};
      encode(fn, &prm.maps[br * 5 + 3], 5, vc, dims, str, box);
    }
    {
      cuuint64_t dims[2] = {448, 4096}, str[1] = {896};
      cuuint32_t box[2] = {64, 128};
      encode(fn, &prm.maps[br * 5 + 4], 2, wo, dims, str, box);
    }
  }
  for (int i = 0; i < 10; i++) prm.ptr[i] = (const unsigned char*)d_in[i];
  prm.out = (__nv_bfloat16*)d_out;
  cudaFuncSetAttribute(fused_attn_kernel, cudaFuncAttributeMaxDynamicSharedMemorySize, SMEM_BYTES);
  fused_attn_kernel<<<128, 384, SMEM_BYTES>>>(prm);
}
```
